```python
import torch

def _softmax(x, axis=-1):
    return torch.softmax(x, dim=axis)
def _gelu(x):
    return torch.nn.functional.gelu(x, approximate="tanh")
def _silu(x):
    return torch.nn.functional.silu(x)
def _sigmoid(x):
    return torch.sigmoid(x)
def _layernorm(x, axis=-1, eps=1e-5):
    m = x.mean(dim=axis, keepdim=True)
    v = x.var(dim=axis, keepdim=True, unbiased=False)
    return (x - m) / torch.sqrt(v + eps)
def _scatter_add(tgt, idx, src, axis=0):
    return tgt.clone().index_add_(axis, idx, src)
def _segment_sum(src, seg, n):
    out = torch.zeros((n,) + src.shape[1:], dtype=src.dtype)
    return out.index_add_(0, seg, src)
def _pad(x, pw):
    flat = tuple(v for pair in reversed(pw) for v in pair)
    return torch.nn.functional.pad(x, flat)

kernel_name = 'concat_heads__linear_kernel_hedgehog__softmax_full_mha__prompt'

def setup_inputs():

    _w = (lambda a: (lambda t: t.to(torch.bfloat16) if t.is_floating_point() else t)(torch.as_tensor(a)))
    def _A_setup():
        B, S, D, H = 1, 2048, 1024, 32
        Dh = D // H
        return {
            "x": _w((lambda *s: torch.randn(*s, dtype=torch.bfloat16) * 0.4)(B, S, D)),
            "wqkv": _w((lambda *s: torch.randn(*s, dtype=torch.bfloat16) * 0.4)(D, 3 * D)),
            "w_phi": _w((lambda *s: torch.randn(*s, dtype=torch.bfloat16) * 0.4)(H, Dh, Dh) * (Dh ** -0.5)),
            "wo": _w((lambda *s: torch.randn(*s, dtype=torch.bfloat16) * 0.05)(D, D)),
        }
    _A_in = _A_setup()

    def _B_setup():
        B, S, D = 1, 2048, 1024
        return {
            "x": _w((lambda *s: torch.randn(*s, dtype=torch.bfloat16) * 0.2)(B, S, D)),
            "wqkv": _w((lambda *s: torch.randn(*s, dtype=torch.bfloat16) * 0.2)(D, 3 * D)),
            "wo": _w((lambda *s: torch.randn(*s, dtype=torch.bfloat16) * 0.05)(D, D)),
        }
    _B_in = _B_setup()

    return {
        "A_x": _A_in["x"],
        "A_wqkv": _A_in["wqkv"],
        "A_w_phi": _A_in["w_phi"],
        "A_wo": _A_in["wo"],
        "B_x": _B_in["x"],
        "B_wqkv": _B_in["wqkv"],
        "B_wo": _B_in["wo"],
    }

def reference(A_x, A_wqkv, A_w_phi, A_wo, B_x, B_wqkv, B_wo):
    def _A_ref(x, wqkv, w_phi, wo):
        B, S, D = x.shape
        H = 32; Dh = D // H
        qkv = (lambda x, *d: x.permute(*d))((x @ wqkv).reshape(B, S, 3, H, Dh), 2, 0, 3, 1, 4)
        q, k, v = qkv[0], qkv[1], qkv[2]
        pq = torch.einsum("bhsd,hdf->bhsf", q, w_phi)
        pk = torch.einsum("bhsd,hdf->bhsf", k, w_phi)
        phi_q = torch.concatenate([_softmax(pq, axis=-1), _softmax(-pq, axis=-1)], axis=-1)
        phi_k = torch.concatenate([_softmax(pk, axis=-1), _softmax(-pk, axis=-1)], axis=-1)
        kv = torch.einsum("bhsf,bhsd->bhfd", phi_k, v)
        z  = torch.einsum("bhsf->bhf", phi_k)
        num = torch.einsum("bhqf,bhfd->bhqd", phi_q, kv)
        den = torch.einsum("bhqf,bhf->bhq", phi_q, z)[..., None] + 1e-6
        o = num / den
        return (lambda x, *d: x.permute(*d))(o, 0, 2, 1, 3).reshape(B, S, D) @ wo

    def _B_ref(x, wqkv, wo):
        B, S, D = x.shape
        H = 32; Dh = D // H
        qkv = (lambda x, *d: x.permute(*d))((x @ wqkv).reshape(B, S, 3, H, Dh), 2, 0, 3, 1, 4)
        q, k, v = qkv[0], qkv[1], qkv[2]
        scale = Dh ** -0.5
        scores = torch.einsum("bhqd,bhkd->bhqk", q, k) * scale
        p = _softmax(scores, axis=-1)
        o = torch.einsum("bhqk,bhkd->bhqd", p, v)
        return (lambda x, *d: x.permute(*d))(o, 0, 2, 1, 3).reshape(B, S, D) @ wo

    a = _A_ref(A_x, A_wqkv, A_w_phi, A_wo)
    b = _B_ref(B_x, B_wqkv, B_wo)
    return torch.concatenate([a, b], axis=-1)
```

```cpp
#include <cuda_runtime.h>
#include <cuda_bf16.h>
#include <cuda.h>
#include <stdint.h>

namespace {

constexpr int SEQ = 2048;
constexpr int DM = 1024;
constexpr int NH = 32;

__device__ __align__(1024) __nv_bfloat16 g_qkv[2 * 3 * NH * SEQ * 32];
__device__ __align__(1024) __nv_bfloat16 g_o[2 * SEQ * DM];
__device__ float g_norm[3 * NH * 128];
__device__ __align__(16) float g_kvp[NH * 8 * 64 * 40];

struct TMaps {
    CUtensorMap x[2];
    CUtensorMap w[2];
    CUtensorMap phi;
    CUtensorMap qkv64;
    CUtensorMap qkv128;
    CUtensorMap o;
    CUtensorMap wo[2];
    CUtensorMap out;
};

__device__ __forceinline__ uint32_t smem_u32(const void* p) { return (uint32_t)__cvta_generic_to_shared(p); }
__device__ __forceinline__ void mbar_init(uint32_t bar, uint32_t cnt) {
    asm volatile("mbarrier.init.shared::cta.b64 [%0], %1;" ::"r"(bar), "r"(cnt) : "memory");
}
__device__ __forceinline__ void mbar_expect_tx(uint32_t bar, uint32_t bytes) {
    asm volatile("mbarrier.arrive.expect_tx.shared::cta.b64 _, [%0], %1;" ::"r"(bar), "r"(bytes) : "memory");
}
__device__ __forceinline__ void mbar_arrive(uint32_t bar) {
    asm volatile("mbarrier.arrive.shared::cta.b64 _, [%0];" ::"r"(bar) : "memory");
}
__device__ __forceinline__ void mbar_wait(uint32_t bar, uint32_t parity) {
    asm volatile(
        "{\n"
        ".reg .pred p;\n"
        ".reg .u32 n;\n"
        "mbarrier.try_wait.parity.shared::cta.b64 p, [%0], %1;\n"
        "@p bra DONE;\n"
        "mov.u32 n, 0;\n"
        "LAB_WAIT:\n"
        "mbarrier.try_wait.parity.shared::cta.b64 p, [%0], %1;\n"
        "@p bra DONE;\n"
        "add.u32 n, n, 1;\n"
        "setp.lt.u32 p, n, 4194304;\n"
        "@p bra LAB_WAIT;\n"
        "trap;\n"
        "DONE:\n"
        "}\n" ::"r"(bar), "r"(parity) : "memory");
}
__device__ __forceinline__ void tma_load(uint32_t dst, const CUtensorMap* m, uint32_t bar, int c0, int c1) {
    asm volatile("cp.async.bulk.tensor.2d.shared::cluster.global.mbarrier::complete_tx::bytes [%0], [%1, {%3, %4}], [%2];"
                 ::"r"(dst), "l"(m), "r"(bar), "r"(c0), "r"(c1) : "memory");
}
__device__ __forceinline__ void tma_store(const CUtensorMap* m, uint32_t src, int c0, int c1) {
    asm volatile("cp.async.bulk.tensor.2d.global.shared::cta.bulk_group [%0, {%2, %3}], [%1];"
                 ::"l"(m), "r"(src), "r"(c0), "r"(c1) : "memory");
}
__device__ __forceinline__ void bulk_commit() { asm volatile("cp.async.bulk.commit_group;" ::: "memory"); }
template <int N> __device__ __forceinline__ void bulk_wait_read() { asm volatile("cp.async.bulk.wait_group.read %0;" ::"n"(N) : "memory"); }
template <int N> __device__ __forceinline__ void bulk_wait() { asm volatile("cp.async.bulk.wait_group %0;" ::"n"(N) : "memory"); }
__device__ __forceinline__ void prefetch_tmap(const CUtensorMap* m) { asm volatile("prefetch.tensormap [%0];" ::"l"(m) : "memory"); }
__device__ __forceinline__ void fence_async_smem() { asm volatile("fence.proxy.async.shared::cta;" ::: "memory"); }
__device__ __forceinline__ void fence_mbar_init() { asm volatile("fence.mbarrier_init.release.cluster;" ::: "memory"); }
__device__ __forceinline__ void bar_sync(int id, int n) { asm volatile("bar.sync %0, %1;" ::"r"(id), "r"(n) : "memory"); }
__device__ __forceinline__ void bar_arrive(int id, int n) { asm volatile("bar.arrive %0, %1;" ::"r"(id), "r"(n) : "memory"); }
__device__ __forceinline__ void pdl_wait() { asm volatile("griddepcontrol.wait;" ::: "memory"); }
__device__ __forceinline__ void pdl_launch() { asm volatile("griddepcontrol.launch_dependents;" ::: "memory"); }
template <int R> __device__ __forceinline__ void reg_inc() { asm volatile("setmaxnreg.inc.sync.aligned.u32 %0;" ::"n"(R)); }
template <int R> __device__ __forceinline__ void reg_dec() { asm volatile("setmaxnreg.dec.sync.aligned.u32 %0;" ::"n"(R)); }

__device__ __forceinline__ void wg_fence() { asm volatile("wgmma.fence.sync.aligned;" ::: "memory"); }
__device__ __forceinline__ void wg_commit() { asm volatile("wgmma.commit_group.sync.aligned;" ::: "memory"); }
template <int N> __device__ __forceinline__ void wg_wait() { asm volatile("wgmma.wait_group.sync.aligned %0;" ::"n"(N) : "memory"); }
template <int N> __device__ __forceinline__ void fence_regs(float* d) {
#pragma unroll
    for (int i = 0; i < N; i++) asm volatile("" : "+f"(d[i])::"memory");
}
template <int N> __device__ __forceinline__ void fence_regs_u(uint32_t* d) {
#pragma unroll
    for (int i = 0; i < N; i++) asm volatile("" : "+r"(d[i])::"memory");
}
__device__ __forceinline__ uint64_t mkdesc(uint32_t addr, uint32_t lbo, uint32_t sbo, uint32_t swz) {
    uint64_t d = 0;
    d |= (uint64_t)((addr & 0x3FFFF) >> 4);
    d |= (uint64_t)((lbo >> 4) & 0x3FFF) << 16;
    d |= (uint64_t)((sbo >> 4) & 0x3FFF) << 32;
    d |= (uint64_t)swz << 62;
    return d;
}
__device__ __forceinline__ uint32_t pack_bf16(float lo, float hi) {
    uint32_t r;
    asm("cvt.rn.bf16x2.f32 %0, %1, %2;" : "=r"(r) : "f"(hi), "f"(lo));
    return r;
}
__device__ __forceinline__ void stsm_x4(uint32_t addr, uint32_t r0, uint32_t r1, uint32_t r2, uint32_t r3) {
    asm volatile("stmatrix.sync.aligned.m8n8.x4.shared.b16 [%0], {%1, %2, %3, %4};" ::"r"(addr), "r"(r0), "r"(r1), "r"(r2), "r"(r3) : "memory");
}
__device__ __forceinline__ void ldsm_x4(uint32_t addr, uint32_t& r0, uint32_t& r1, uint32_t& r2, uint32_t& r3) {
    asm volatile("ldmatrix.sync.aligned.m8n8.x4.shared.b16 {%0, %1, %2, %3}, [%4];" : "=r"(r0), "=r"(r1), "=r"(r2), "=r"(r3) : "r"(addr) : "memory");
}
__device__ __forceinline__ float ex2(float x) {
    float y;
    asm("ex2.approx.ftz.f32 %0, %1;" : "=f"(y) : "f"(x));
    return y;
}
__device__ __forceinline__ float ex2_poly(float x) {
    float t = x + 12582912.f;
    float r = t - 12582912.f;
    float f = x - r;
    float p = fmaf(0.055171772837638855f, f, 0.2426113784313202f);
    p = fmaf(p, f, 0.6932609677314758f);
    p = fmaf(p, f, 0.9999279975891113f);
    return __int_as_float(__float_as_int(p) + (__float_as_int(t) << 23));
}

struct TrueT { static constexpr bool value = true; };
struct FalseT { static constexpr bool value = false; };

__device__ __forceinline__ void wg_ss128_z(float* d, uint64_t da, uint64_t db) {
    asm volatile("wgmma.mma_async.sync.aligned.m64n128k16.f32.bf16.bf16 {%0, %1, %2, %3, %4, %5, %6, %7, %8, %9, %10, %11, %12, %13, %14, %15, %16, %17, %18, %19, %20, %21, %22, %23, %24, %25, %26, %27, %28, %29, %30, %31, %32, %33, %34, %35, %36, %37, %38, %39, %40, %41, %42, %43, %44, %45, %46, %47, %48, %49, %50, %51, %52, %53, %54, %55, %56, %57, %58, %59, %60, %61, %62, %63}, %64, %65, 0, 1, 1, 0, 1;"
        : "=f"(d[0]), "=f"(d[1]), "=f"(d[2]), "=f"(d[3]), "=f"(d[4]), "=f"(d[5]), "=f"(d[6]), "=f"(d[7]), "=f"(d[8]), "=f"(d[9]), "=f"(d[10]), "=f"(d[11]), "=f"(d[12]), "=f"(d[13]), "=f"(d[14]), "=f"(d[15]), "=f"(d[16]), "=f"(d[17]), "=f"(d[18]), "=f"(d[19]), "=f"(d[20]), "=f"(d[21]), "=f"(d[22]), "=f"(d[23]), "=f"(d[24]), "=f"(d[25]), "=f"(d[26]), "=f"(d[27]), "=f"(d[28]), "=f"(d[29]), "=f"(d[30]), "=f"(d[31]), "=f"(d[32]), "=f"(d[33]), "=f"(d[34]), "=f"(d[35]), "=f"(d[36]), "=f"(d[37]), "=f"(d[38]), "=f"(d[39]), "=f"(d[40]), "=f"(d[41]), "=f"(d[42]), "=f"(d[43]), "=f"(d[44]), "=f"(d[45]), "=f"(d[46]), "=f"(d[47]), "=f"(d[48]), "=f"(d[49]), "=f"(d[50]), "=f"(d[51]), "=f"(d[52]), "=f"(d[53]), "=f"(d[54]), "=f"(d[55]), "=f"(d[56]), "=f"(d[57]), "=f"(d[58]), "=f"(d[59]), "=f"(d[60]), "=f"(d[61]), "=f"(d[62]), "=f"(d[63]) : "l"(da), "l"(db));
}
__device__ __forceinline__ void wg_ss128(float* d, uint64_t da, uint64_t db) {
    asm volatile("wgmma.mma_async.sync.aligned.m64n128k16.f32.bf16.bf16 {%0, %1, %2, %3, %4, %5, %6, %7, %8, %9, %10, %11, %12, %13, %14, %15, %16, %17, %18, %19, %20, %21, %22, %23, %24, %25, %26, %27, %28, %29, %30, %31, %32, %33, %34, %35, %36, %37, %38, %39, %40, %41, %42, %43, %44, %45, %46, %47, %48, %49, %50, %51, %52, %53, %54, %55, %56, %57, %58, %59, %60, %61, %62, %63}, %64, %65, 1, 1, 1, 0, 1;"
        : "+f"(d[0]), "+f"(d[1]), "+f"(d[2]), "+f"(d[3]), "+f"(d[4]), "+f"(d[5]), "+f"(d[6]), "+f"(d[7]), "+f"(d[8]), "+f"(d[9]), "+f"(d[10]), "+f"(d[11]), "+f"(d[12]), "+f"(d[13]), "+f"(d[14]), "+f"(d[15]), "+f"(d[16]), "+f"(d[17]), "+f"(d[18]), "+f"(d[19]), "+f"(d[20]), "+f"(d[21]), "+f"(d[22]), "+f"(d[23]), "+f"(d[24]), "+f"(d[25]), "+f"(d[26]), "+f"(d[27]), "+f"(d[28]), "+f"(d[29]), "+f"(d[30]), "+f"(d[31]), "+f"(d[32]), "+f"(d[33]), "+f"(d[34]), "+f"(d[35]), "+f"(d[36]), "+f"(d[37]), "+f"(d[38]), "+f"(d[39]), "+f"(d[40]), "+f"(d[41]), "+f"(d[42]), "+f"(d[43]), "+f"(d[44]), "+f"(d[45]), "+f"(d[46]), "+f"(d[47]), "+f"(d[48]), "+f"(d[49]), "+f"(d[50]), "+f"(d[51]), "+f"(d[52]), "+f"(d[53]), "+f"(d[54]), "+f"(d[55]), "+f"(d[56]), "+f"(d[57]), "+f"(d[58]), "+f"(d[59]), "+f"(d[60]), "+f"(d[61]), "+f"(d[62]), "+f"(d[63]) : "l"(da), "l"(db));
}
__device__ __forceinline__ void wg_ss192_z(float* d, uint64_t da, uint64_t db) {
    asm volatile("wgmma.mma_async.sync.aligned.m64n192k16.f32.bf16.bf16 {%0, %1, %2, %3, %4, %5, %6, %7, %8, %9, %10, %11, %12, %13, %14, %15, %16, %17, %18, %19, %20, %21, %22, %23, %24, %25, %26, %27, %28, %29, %30, %31, %32, %33, %34, %35, %36, %37, %38, %39, %40, %41, %42, %43, %44, %45, %46, %47, %48, %49, %50, %51, %52, %53, %54, %55, %56, %57, %58, %59, %60, %61, %62, %63, %64, %65, %66, %67, %68, %69, %70, %71, %72, %73, %74, %75, %76, %77, %78, %79, %80, %81, %82, %83, %84, %85, %86, %87, %88, %89, %90, %91, %92, %93, %94, %95}, %96, %97, 0, 1, 1, 0, 1;"
        : "=f"(d[0]), "=f"(d[1]), "=f"(d[2]), "=f"(d[3]), "=f"(d[4]), "=f"(d[5]), "=f"(d[6]), "=f"(d[7]), "=f"(d[8]), "=f"(d[9]), "=f"(d[10]), "=f"(d[11]), "=f"(d[12]), "=f"(d[13]), "=f"(d[14]), "=f"(d[15]), "=f"(d[16]), "=f"(d[17]), "=f"(d[18]), "=f"(d[19]), "=f"(d[20]), "=f"(d[21]), "=f"(d[22]), "=f"(d[23]), "=f"(d[24]), "=f"(d[25]), "=f"(d[26]), "=f"(d[27]), "=f"(d[28]), "=f"(d[29]), "=f"(d[30]), "=f"(d[31]), "=f"(d[32]), "=f"(d[33]), "=f"(d[34]), "=f"(d[35]), "=f"(d[36]), "=f"(d[37]), "=f"(d[38]), "=f"(d[39]), "=f"(d[40]), "=f"(d[41]), "=f"(d[42]), "=f"(d[43]), "=f"(d[44]), "=f"(d[45]), "=f"(d[46]), "=f"(d[47]), "=f"(d[48]), "=f"(d[49]), "=f"(d[50]), "=f"(d[51]), "=f"(d[52]), "=f"(d[53]), "=f"(d[54]), "=f"(d[55]), "=f"(d[56]), "=f"(d[57]), "=f"(d[58]), "=f"(d[59]), "=f"(d[60]), "=f"(d[61]), "=f"(d[62]), "=f"(d[63]), "=f"(d[64]), "=f"(d[65]), "=f"(d[66]), "=f"(d[67]), "=f"(d[68]), "=f"(d[69]), "=f"(d[70]), "=f"(d[71]), "=f"(d[72]), "=f"(d[73]), "=f"(d[74]), "=f"(d[75]), "=f"(d[76]), "=f"(d[77]), "=f"(d[78]), "=f"(d[79]), "=f"(d[80]), "=f"(d[81]), "=f"(d[82]), "=f"(d[83]), "=f"(d[84]), "=f"(d[85]), "=f"(d[86]), "=f"(d[87]), "=f"(d[88]), "=f"(d[89]), "=f"(d[90]), "=f"(d[91]), "=f"(d[92]), "=f"(d[93]), "=f"(d[94]), "=f"(d[95]) : "l"(da), "l"(db));
}
__device__ __forceinline__ void wg_ss192(float* d, uint64_t da, uint64_t db) {
    asm volatile("wgmma.mma_async.sync.aligned.m64n192k16.f32.bf16.bf16 {%0, %1, %2, %3, %4, %5, %6, %7, %8, %9, %10, %11, %12, %13, %14, %15, %16, %17, %18, %19, %20, %21, %22, %23, %24, %25, %26, %27, %28, %29, %30, %31, %32, %33, %34, %35, %36, %37, %38, %39, %40, %41, %42, %43, %44, %45, %46, %47, %48, %49, %50, %51, %52, %53, %54, %55, %56, %57, %58, %59, %60, %61, %62, %63, %64, %65, %66, %67, %68, %69, %70, %71, %72, %73, %74, %75, %76, %77, %78, %79, %80, %81, %82, %83, %84, %85, %86, %87, %88, %89, %90, %91, %92, %93, %94, %95}, %96, %97, 1, 1, 1, 0, 1;"
        : "+f"(d[0]), "+f"(d[1]), "+f"(d[2]), "+f"(d[3]), "+f"(d[4]), "+f"(d[5]), "+f"(d[6]), "+f"(d[7]), "+f"(d[8]), "+f"(d[9]), "+f"(d[10]), "+f"(d[11]), "+f"(d[12]), "+f"(d[13]), "+f"(d[14]), "+f"(d[15]), "+f"(d[16]), "+f"(d[17]), "+f"(d[18]), "+f"(d[19]), "+f"(d[20]), "+f"(d[21]), "+f"(d[22]), "+f"(d[23]), "+f"(d[24]), "+f"(d[25]), "+f"(d[26]), "+f"(d[27]), "+f"(d[28]), "+f"(d[29]), "+f"(d[30]), "+f"(d[31]), "+f"(d[32]), "+f"(d[33]), "+f"(d[34]), "+f"(d[35]), "+f"(d[36]), "+f"(d[37]), "+f"(d[38]), "+f"(d[39]), "+f"(d[40]), "+f"(d[41]), "+f"(d[42]), "+f"(d[43]), "+f"(d[44]), "+f"(d[45]), "+f"(d[46]), "+f"(d[47]), "+f"(d[48]), "+f"(d[49]), "+f"(d[50]), "+f"(d[51]), "+f"(d[52]), "+f"(d[53]), "+f"(d[54]), "+f"(d[55]), "+f"(d[56]), "+f"(d[57]), "+f"(d[58]), "+f"(d[59]), "+f"(d[60]), "+f"(d[61]), "+f"(d[62]), "+f"(d[63]), "+f"(d[64]), "+f"(d[65]), "+f"(d[66]), "+f"(d[67]), "+f"(d[68]), "+f"(d[69]), "+f"(d[70]), "+f"(d[71]), "+f"(d[72]), "+f"(d[73]), "+f"(d[74]), "+f"(d[75]), "+f"(d[76]), "+f"(d[77]), "+f"(d[78]), "+f"(d[79]), "+f"(d[80]), "+f"(d[81]), "+f"(d[82]), "+f"(d[83]), "+f"(d[84]), "+f"(d[85]), "+f"(d[86]), "+f"(d[87]), "+f"(d[88]), "+f"(d[89]), "+f"(d[90]), "+f"(d[91]), "+f"(d[92]), "+f"(d[93]), "+f"(d[94]), "+f"(d[95]) : "l"(da), "l"(db));
}
__device__ __forceinline__ void wg_ss256_z(float* d, uint64_t da, uint64_t db) {
    asm volatile("wgmma.mma_async.sync.aligned.m64n256k16.f32.bf16.bf16 {%0, %1, %2, %3, %4, %5, %6, %7, %8, %9, %10, %11, %12, %13, %14, %15, %16, %17, %18, %19, %20, %21, %22, %23, %24, %25, %26, %27, %28, %29, %30, %31, %32, %33, %34, %35, %36, %37, %38, %39, %40, %41, %42, %43, %44, %45, %46, %47, %48, %49, %50, %51, %52, %53, %54, %55, %56, %57, %58, %59, %60, %61, %62, %63, %64, %65, %66, %67, %68, %69, %70, %71, %72, %73, %74, %75, %76, %77, %78, %79, %80, %81, %82, %83, %84, %85, %86, %87, %88, %89, %90, %91, %92, %93, %94, %95, %96, %97, %98, %99, %100, %101, %102, %103, %104, %105, %106, %107, %108, %109, %110, %111, %112, %113, %114, %115, %116, %117, %118, %119, %120, %121, %122, %123, %124, %125, %126, %127}, %128, %129, 0, 1, 1, 0, 1;"
        : "=f"(d[0]), "=f"(d[1]), "=f"(d[2]), "=f"(d[3]), "=f"(d[4]), "=f"(d[5]), "=f"(d[6]), "=f"(d[7]), "=f"(d[8]), "=f"(d[9]), "=f"(d[10]), "=f"(d[11]), "=f"(d[12]), "=f"(d[13]), "=f"(d[14]), "=f"(d[15]), "=f"(d[16]), "=f"(d[17]), "=f"(d[18]), "=f"(d[19]), "=f"(d[20]), "=f"(d[21]), "=f"(d[22]), "=f"(d[23]), "=f"(d[24]), "=f"(d[25]), "=f"(d[26]), "=f"(d[27]), "=f"(d[28]), "=f"(d[29]), "=f"(d[30]), "=f"(d[31]), "=f"(d[32]), "=f"(d[33]), "=f"(d[34]), "=f"(d[35]), "=f"(d[36]), "=f"(d[37]), "=f"(d[38]), "=f"(d[39]), "=f"(d[40]), "=f"(d[41]), "=f"(d[42]), "=f"(d[43]), "=f"(d[44]), "=f"(d[45]), "=f"(d[46]), "=f"(d[47]), "=f"(d[48]), "=f"(d[49]), "=f"(d[50]), "=f"(d[51]), "=f"(d[52]), "=f"(d[53]), "=f"(d[54]), "=f"(d[55]), "=f"(d[56]), "=f"(d[57]), "=f"(d[58]), "=f"(d[59]), "=f"(d[60]), "=f"(d[61]), "=f"(d[62]), "=f"(d[63]), "=f"(d[64]), "=f"(d[65]), "=f"(d[66]), "=f"(d[67]), "=f"(d[68]), "=f"(d[69]), "=f"(d[70]), "=f"(d[71]), "=f"(d[72]), "=f"(d[73]), "=f"(d[74]), "=f"(d[75]), "=f"(d[76]), "=f"(d[77]), "=f"(d[78]), "=f"(d[79]), "=f"(d[80]), "=f"(d[81]), "=f"(d[82]), "=f"(d[83]), "=f"(d[84]), "=f"(d[85]), "=f"(d[86]), "=f"(d[87]), "=f"(d[88]), "=f"(d[89]), "=f"(d[90]), "=f"(d[91]), "=f"(d[92]), "=f"(d[93]), "=f"(d[94]), "=f"(d[95]), "=f"(d[96]), "=f"(d[97]), "=f"(d[98]), "=f"(d[99]), "=f"(d[100]), "=f"(d[101]), "=f"(d[102]), "=f"(d[103]), "=f"(d[104]), "=f"(d[105]), "=f"(d[106]), "=f"(d[107]), "=f"(d[108]), "=f"(d[109]), "=f"(d[110]), "=f"(d[111]), "=f"(d[112]), "=f"(d[113]), "=f"(d[114]), "=f"(d[115]), "=f"(d[116]), "=f"(d[117]), "=f"(d[118]), "=f"(d[119]), "=f"(d[120]), "=f"(d[121]), "=f"(d[122]), "=f"(d[123]), "=f"(d[124]), "=f"(d[125]), "=f"(d[126]), "=f"(d[127]) : "l"(da), "l"(db));
}
__device__ __forceinline__ void wg_ss256(float* d, uint64_t da, uint64_t db) {
    asm volatile("wgmma.mma_async.sync.aligned.m64n256k16.f32.bf16.bf16 {%0, %1, %2, %3, %4, %5, %6, %7, %8, %9, %10, %11, %12, %13, %14, %15, %16, %17, %18, %19, %20, %21, %22, %23, %24, %25, %26, %27, %28, %29, %30, %31, %32, %33, %34, %35, %36, %37, %38, %39, %40, %41, %42, %43, %44, %45, %46, %47, %48, %49, %50, %51, %52, %53, %54, %55, %56, %57, %58, %59, %60, %61, %62, %63, %64, %65, %66, %67, %68, %69, %70, %71, %72, %73, %74, %75, %76, %77, %78, %79, %80, %81, %82, %83, %84, %85, %86, %87, %88, %89, %90, %91, %92, %93, %94, %95, %96, %97, %98, %99, %100, %101, %102, %103, %104, %105, %106, %107, %108, %109, %110, %111, %112, %113, %114, %115, %116, %117, %118, %119, %120, %121, %122, %123, %124, %125, %126, %127}, %128, %129, 1, 1, 1, 0, 1;"
        : "+f"(d[0]), "+f"(d[1]), "+f"(d[2]), "+f"(d[3]), "+f"(d[4]), "+f"(d[5]), "+f"(d[6]), "+f"(d[7]), "+f"(d[8]), "+f"(d[9]), "+f"(d[10]), "+f"(d[11]), "+f"(d[12]), "+f"(d[13]), "+f"(d[14]), "+f"(d[15]), "+f"(d[16]), "+f"(d[17]), "+f"(d[18]), "+f"(d[19]), "+f"(d[20]), "+f"(d[21]), "+f"(d[22]), "+f"(d[23]), "+f"(d[24]), "+f"(d[25]), "+f"(d[26]), "+f"(d[27]), "+f"(d[28]), "+f"(d[29]), "+f"(d[30]), "+f"(d[31]), "+f"(d[32]), "+f"(d[33]), "+f"(d[34]), "+f"(d[35]), "+f"(d[36]), "+f"(d[37]), "+f"(d[38]), "+f"(d[39]), "+f"(d[40]), "+f"(d[41]), "+f"(d[42]), "+f"(d[43]), "+f"(d[44]), "+f"(d[45]), "+f"(d[46]), "+f"(d[47]), "+f"(d[48]), "+f"(d[49]), "+f"(d[50]), "+f"(d[51]), "+f"(d[52]), "+f"(d[53]), "+f"(d[54]), "+f"(d[55]), "+f"(d[56]), "+f"(d[57]), "+f"(d[58]), "+f"(d[59]), "+f"(d[60]), "+f"(d[61]), "+f"(d[62]), "+f"(d[63]), "+f"(d[64]), "+f"(d[65]), "+f"(d[66]), "+f"(d[67]), "+f"(d[68]), "+f"(d[69]), "+f"(d[70]), "+f"(d[71]), "+f"(d[72]), "+f"(d[73]), "+f"(d[74]), "+f"(d[75]), "+f"(d[76]), "+f"(d[77]), "+f"(d[78]), "+f"(d[79]), "+f"(d[80]), "+f"(d[81]), "+f"(d[82]), "+f"(d[83]), "+f"(d[84]), "+f"(d[85]), "+f"(d[86]), "+f"(d[87]), "+f"(d[88]), "+f"(d[89]), "+f"(d[90]), "+f"(d[91]), "+f"(d[92]), "+f"(d[93]), "+f"(d[94]), "+f"(d[95]), "+f"(d[96]), "+f"(d[97]), "+f"(d[98]), "+f"(d[99]), "+f"(d[100]), "+f"(d[101]), "+f"(d[102]), "+f"(d[103]), "+f"(d[104]), "+f"(d[105]), "+f"(d[106]), "+f"(d[107]), "+f"(d[108]), "+f"(d[109]), "+f"(d[110]), "+f"(d[111]), "+f"(d[112]), "+f"(d[113]), "+f"(d[114]), "+f"(d[115]), "+f"(d[116]), "+f"(d[117]), "+f"(d[118]), "+f"(d[119]), "+f"(d[120]), "+f"(d[121]), "+f"(d[122]), "+f"(d[123]), "+f"(d[124]), "+f"(d[125]), "+f"(d[126]), "+f"(d[127]) : "l"(da), "l"(db));
}
__device__ __forceinline__ void wg_rs64_z(float* d, uint32_t a0, uint32_t a1, uint32_t a2, uint32_t a3, uint64_t db) {
    asm volatile("wgmma.mma_async.sync.aligned.m64n64k16.f32.bf16.bf16 {%0, %1, %2, %3, %4, %5, %6, %7, %8, %9, %10, %11, %12, %13, %14, %15, %16, %17, %18, %19, %20, %21, %22, %23, %24, %25, %26, %27, %28, %29, %30, %31}, {%32, %33, %34, %35}, %36, 0, 1, 1, 0;"
        : "=f"(d[0]), "=f"(d[1]), "=f"(d[2]), "=f"(d[3]), "=f"(d[4]), "=f"(d[5]), "=f"(d[6]), "=f"(d[7]), "=f"(d[8]), "=f"(d[9]), "=f"(d[10]), "=f"(d[11]), "=f"(d[12]), "=f"(d[13]), "=f"(d[14]), "=f"(d[15]), "=f"(d[16]), "=f"(d[17]), "=f"(d[18]), "=f"(d[19]), "=f"(d[20]), "=f"(d[21]), "=f"(d[22]), "=f"(d[23]), "=f"(d[24]), "=f"(d[25]), "=f"(d[26]), "=f"(d[27]), "=f"(d[28]), "=f"(d[29]), "=f"(d[30]), "=f"(d[31]) : "r"(a0), "r"(a1), "r"(a2), "r"(a3), "l"(db));
}
__device__ __forceinline__ void wg_rs64(float* d, uint32_t a0, uint32_t a1, uint32_t a2, uint32_t a3, uint64_t db) {
    asm volatile("wgmma.mma_async.sync.aligned.m64n64k16.f32.bf16.bf16 {%0, %1, %2, %3, %4, %5, %6, %7, %8, %9, %10, %11, %12, %13, %14, %15, %16, %17, %18, %19, %20, %21, %22, %23, %24, %25, %26, %27, %28, %29, %30, %31}, {%32, %33, %34, %35}, %36, 1, 1, 1, 0;"
        : "+f"(d[0]), "+f"(d[1]), "+f"(d[2]), "+f"(d[3]), "+f"(d[4]), "+f"(d[5]), "+f"(d[6]), "+f"(d[7]), "+f"(d[8]), "+f"(d[9]), "+f"(d[10]), "+f"(d[11]), "+f"(d[12]), "+f"(d[13]), "+f"(d[14]), "+f"(d[15]), "+f"(d[16]), "+f"(d[17]), "+f"(d[18]), "+f"(d[19]), "+f"(d[20]), "+f"(d[21]), "+f"(d[22]), "+f"(d[23]), "+f"(d[24]), "+f"(d[25]), "+f"(d[26]), "+f"(d[27]), "+f"(d[28]), "+f"(d[29]), "+f"(d[30]), "+f"(d[31]) : "r"(a0), "r"(a1), "r"(a2), "r"(a3), "l"(db));
}
__device__ __forceinline__ void wg_rs128_z(float* d, uint32_t a0, uint32_t a1, uint32_t a2, uint32_t a3, uint64_t db) {
    asm volatile("wgmma.mma_async.sync.aligned.m64n128k16.f32.bf16.bf16 {%0, %1, %2, %3, %4, %5, %6, %7, %8, %9, %10, %11, %12, %13, %14, %15, %16, %17, %18, %19, %20, %21, %22, %23, %24, %25, %26, %27, %28, %29, %30, %31, %32, %33, %34, %35, %36, %37, %38, %39, %40, %41, %42, %43, %44, %45, %46, %47, %48, %49, %50, %51, %52, %53, %54, %55, %56, %57, %58, %59, %60, %61, %62, %63}, {%64, %65, %66, %67}, %68, 0, 1, 1, 0;"
        : "=f"(d[0]), "=f"(d[1]), "=f"(d[2]), "=f"(d[3]), "=f"(d[4]), "=f"(d[5]), "=f"(d[6]), "=f"(d[7]), "=f"(d[8]), "=f"(d[9]), "=f"(d[10]), "=f"(d[11]), "=f"(d[12]), "=f"(d[13]), "=f"(d[14]), "=f"(d[15]), "=f"(d[16]), "=f"(d[17]), "=f"(d[18]), "=f"(d[19]), "=f"(d[20]), "=f"(d[21]), "=f"(d[22]), "=f"(d[23]), "=f"(d[24]), "=f"(d[25]), "=f"(d[26]), "=f"(d[27]), "=f"(d[28]), "=f"(d[29]), "=f"(d[30]), "=f"(d[31]), "=f"(d[32]), "=f"(d[33]), "=f"(d[34]), "=f"(d[35]), "=f"(d[36]), "=f"(d[37]), "=f"(d[38]), "=f"(d[39]), "=f"(d[40]), "=f"(d[41]), "=f"(d[42]), "=f"(d[43]), "=f"(d[44]), "=f"(d[45]), "=f"(d[46]), "=f"(d[47]), "=f"(d[48]), "=f"(d[49]), "=f"(d[50]), "=f"(d[51]), "=f"(d[52]), "=f"(d[53]), "=f"(d[54]), "=f"(d[55]), "=f"(d[56]), "=f"(d[57]), "=f"(d[58]), "=f"(d[59]), "=f"(d[60]), "=f"(d[61]), "=f"(d[62]), "=f"(d[63]) : "r"(a0), "r"(a1), "r"(a2), "r"(a3), "l"(db));
}
__device__ __forceinline__ void wg_rs128(float* d, uint32_t a0, uint32_t a1, uint32_t a2, uint32_t a3, uint64_t db) {
    asm volatile("wgmma.mma_async.sync.aligned.m64n128k16.f32.bf16.bf16 {%0, %1, %2, %3, %4, %5, %6, %7, %8, %9, %10, %11, %12, %13, %14, %15, %16, %17, %18, %19, %20, %21, %22, %23, %24, %25, %26, %27, %28, %29, %30, %31, %32, %33, %34, %35, %36, %37, %38, %39, %40, %41, %42, %43, %44, %45, %46, %47, %48, %49, %50, %51, %52, %53, %54, %55, %56, %57, %58, %59, %60, %61, %62, %63}, {%64, %65, %66, %67}, %68, 1, 1, 1, 0;"
        : "+f"(d[0]), "+f"(d[1]), "+f"(d[2]), "+f"(d[3]), "+f"(d[4]), "+f"(d[5]), "+f"(d[6]), "+f"(d[7]), "+f"(d[8]), "+f"(d[9]), "+f"(d[10]), "+f"(d[11]), "+f"(d[12]), "+f"(d[13]), "+f"(d[14]), "+f"(d[15]), "+f"(d[16]), "+f"(d[17]), "+f"(d[18]), "+f"(d[19]), "+f"(d[20]), "+f"(d[21]), "+f"(d[22]), "+f"(d[23]), "+f"(d[24]), "+f"(d[25]), "+f"(d[26]), "+f"(d[27]), "+f"(d[28]), "+f"(d[29]), "+f"(d[30]), "+f"(d[31]), "+f"(d[32]), "+f"(d[33]), "+f"(d[34]), "+f"(d[35]), "+f"(d[36]), "+f"(d[37]), "+f"(d[38]), "+f"(d[39]), "+f"(d[40]), "+f"(d[41]), "+f"(d[42]), "+f"(d[43]), "+f"(d[44]), "+f"(d[45]), "+f"(d[46]), "+f"(d[47]), "+f"(d[48]), "+f"(d[49]), "+f"(d[50]), "+f"(d[51]), "+f"(d[52]), "+f"(d[53]), "+f"(d[54]), "+f"(d[55]), "+f"(d[56]), "+f"(d[57]), "+f"(d[58]), "+f"(d[59]), "+f"(d[60]), "+f"(d[61]), "+f"(d[62]), "+f"(d[63]) : "r"(a0), "r"(a1), "r"(a2), "r"(a3), "l"(db));
}
__device__ __forceinline__ void wg_rs40t(float* d, uint32_t a0, uint32_t a1, uint32_t a2, uint32_t a3, uint64_t db) {
    asm volatile("wgmma.mma_async.sync.aligned.m64n40k16.f32.bf16.bf16 {%0, %1, %2, %3, %4, %5, %6, %7, %8, %9, %10, %11, %12, %13, %14, %15, %16, %17, %18, %19}, {%20, %21, %22, %23}, %24, 1, 1, 1, 1;"
        : "+f"(d[0]), "+f"(d[1]), "+f"(d[2]), "+f"(d[3]), "+f"(d[4]), "+f"(d[5]), "+f"(d[6]), "+f"(d[7]), "+f"(d[8]), "+f"(d[9]), "+f"(d[10]), "+f"(d[11]), "+f"(d[12]), "+f"(d[13]), "+f"(d[14]), "+f"(d[15]), "+f"(d[16]), "+f"(d[17]), "+f"(d[18]), "+f"(d[19]) : "r"(a0), "r"(a1), "r"(a2), "r"(a3), "l"(db));
}
__device__ __forceinline__ void wg_rs40t_z(float* d, uint32_t a0, uint32_t a1, uint32_t a2, uint32_t a3, uint64_t db) {
    asm volatile("wgmma.mma_async.sync.aligned.m64n40k16.f32.bf16.bf16 {%0, %1, %2, %3, %4, %5, %6, %7, %8, %9, %10, %11, %12, %13, %14, %15, %16, %17, %18, %19}, {%20, %21, %22, %23}, %24, 0, 1, 1, 1;"
        : "=f"(d[0]), "=f"(d[1]), "=f"(d[2]), "=f"(d[3]), "=f"(d[4]), "=f"(d[5]), "=f"(d[6]), "=f"(d[7]), "=f"(d[8]), "=f"(d[9]), "=f"(d[10]), "=f"(d[11]), "=f"(d[12]), "=f"(d[13]), "=f"(d[14]), "=f"(d[15]), "=f"(d[16]), "=f"(d[17]), "=f"(d[18]), "=f"(d[19]) : "r"(a0), "r"(a1), "r"(a2), "r"(a3), "l"(db));
}
__device__ __forceinline__ void wg_rs32t_z(float* d, uint32_t a0, uint32_t a1, uint32_t a2, uint32_t a3, uint64_t db) {
    asm volatile("wgmma.mma_async.sync.aligned.m64n32k16.f32.bf16.bf16 {%0, %1, %2, %3, %4, %5, %6, %7, %8, %9, %10, %11, %12, %13, %14, %15}, {%16, %17, %18, %19}, %20, 0, 1, 1, 1;"
        : "=f"(d[0]), "=f"(d[1]), "=f"(d[2]), "=f"(d[3]), "=f"(d[4]), "=f"(d[5]), "=f"(d[6]), "=f"(d[7]), "=f"(d[8]), "=f"(d[9]), "=f"(d[10]), "=f"(d[11]), "=f"(d[12]), "=f"(d[13]), "=f"(d[14]), "=f"(d[15]) : "r"(a0), "r"(a1), "r"(a2), "r"(a3), "l"(db));
}
__device__ __forceinline__ void wg_rs32t(float* d, uint32_t a0, uint32_t a1, uint32_t a2, uint32_t a3, uint64_t db) {
    asm volatile("wgmma.mma_async.sync.aligned.m64n32k16.f32.bf16.bf16 {%0, %1, %2, %3, %4, %5, %6, %7, %8, %9, %10, %11, %12, %13, %14, %15}, {%16, %17, %18, %19}, %20, 1, 1, 1, 1;"
        : "+f"(d[0]), "+f"(d[1]), "+f"(d[2]), "+f"(d[3]), "+f"(d[4]), "+f"(d[5]), "+f"(d[6]), "+f"(d[7]), "+f"(d[8]), "+f"(d[9]), "+f"(d[10]), "+f"(d[11]), "+f"(d[12]), "+f"(d[13]), "+f"(d[14]), "+f"(d[15]) : "r"(a0), "r"(a1), "r"(a2), "r"(a3), "l"(db));
}
__device__ __forceinline__ void wg_ss40tt(float* d, uint64_t da, uint64_t db) {
    asm volatile("wgmma.mma_async.sync.aligned.m64n40k16.f32.bf16.bf16 {%0, %1, %2, %3, %4, %5, %6, %7, %8, %9, %10, %11, %12, %13, %14, %15, %16, %17, %18, %19}, %20, %21, 1, 1, 1, 1, 1;"
        : "+f"(d[0]), "+f"(d[1]), "+f"(d[2]), "+f"(d[3]), "+f"(d[4]), "+f"(d[5]), "+f"(d[6]), "+f"(d[7]), "+f"(d[8]), "+f"(d[9]), "+f"(d[10]), "+f"(d[11]), "+f"(d[12]), "+f"(d[13]), "+f"(d[14]), "+f"(d[15]), "+f"(d[16]), "+f"(d[17]), "+f"(d[18]), "+f"(d[19]) : "l"(da), "l"(db));
}


constexpr float QSCALE = 0.17677669529663687f * 1.4426950408889634f;

template <int MB, int STAGES> struct QkvCfg {
    static constexpr int BM = 128 * MB;
    static constexpr int A_BYTES = BM * 128;
    static constexpr int B_BYTES = 3 * 8192;
    static constexpr int STAGE = A_BYTES + B_BYTES;
    static constexpr int OFF_STG = STAGES * STAGE;
    static constexpr int OFF_PHI = OFF_STG + 2 * 24576;
    static constexpr int OFF_BAR = OFF_PHI + 4096;
    static constexpr int SMEM = OFF_BAR + 128 + 1024;
    static constexpr int MT = SEQ / BM;
    static constexpr int TPP = MT * 16;
};

template <int MB, int STAGES, int RC, int RP>
__global__ void __launch_bounds__(384, 1)
qkv_gemm_kernel(const __grid_constant__ TMaps tm, int tile_begin, int tile_end, int first_prob) {
    using C = QkvCfg<MB, STAGES>;
    extern __shared__ uint8_t smem_raw[];
    const uint32_t sb = (smem_u32(smem_raw) + 1023) & ~1023u;
    const uint32_t bar_full = sb + C::OFF_BAR, bar_empty = bar_full + 8 * STAGES;
    const uint32_t bar_phi_full = bar_empty + 8 * STAGES, bar_phi_empty = bar_phi_full + 8;
    const int wg = threadIdx.x >> 7;
    const int warp = (threadIdx.x >> 5) & 3, lane = threadIdx.x & 31;

    if (threadIdx.x == 0) {
        for (int s = 0; s < STAGES; s++) { mbar_init(bar_full + 8 * s, 1); mbar_init(bar_empty + 8 * s, 8); }
        mbar_init(bar_phi_full, 1);
        mbar_init(bar_phi_empty, 8);
        fence_mbar_init();
    }
    __syncthreads();
    pdl_launch();

    if (wg == 2) {
        reg_dec<RP>();
        if (warp == 0 && lane == 0) {
            prefetch_tmap(&tm.x[0]); prefetch_tmap(&tm.x[1]); prefetch_tmap(&tm.w[0]); prefetch_tmap(&tm.w[1]);
            int s = 0; uint32_t ph = 1; uint32_t phi_ph = 1;
            for (int t = tile_begin + blockIdx.x; t < tile_end; t += gridDim.x) {
                const int pi = t / C::TPP, tt = t % C::TPP;
                const int prob = pi == 0 ? first_prob : 1 - first_prob;
                const int mt = tt % C::MT, nt = tt / C::MT;
                const CUtensorMap* mx = &tm.x[prob];
                const CUtensorMap* mw = &tm.w[prob];
                for (int kt = 0; kt < 16; kt++) {
                    mbar_wait(bar_empty + 8 * s, ph);
                    const uint32_t st = sb + s * C::STAGE, fb = bar_full + 8 * s;
                    mbar_expect_tx(fb, C::STAGE);
                    tma_load(st, mx, fb, kt * 64, mt * C::BM);
#pragma unroll
                    for (int p = 0; p < 3; p++) tma_load(st + C::A_BYTES + p * 8192, mw, fb, p * 1024 + nt * 64, kt * 64);
                    if (++s == STAGES) { s = 0; ph ^= 1; }
                    if (kt == 2 && prob == 0) {
                        mbar_wait(bar_phi_empty, phi_ph);
                        mbar_expect_tx(bar_phi_full, 4096);
                        tma_load(sb + C::OFF_PHI, &tm.phi, bar_phi_full, 0, nt * 64);
                        phi_ph ^= 1;
                    }
                }
            }
        }
    } else {
        reg_inc<RC>();
        float acc[MB][96];
        int s = 0; uint32_t ph = 0; uint32_t phi_ph = 0;
        bool stores_pending = false;
        for (int t = tile_begin + blockIdx.x; t < tile_end; t += gridDim.x) {
            const int pi = t / C::TPP, tt = t % C::TPP;
            const int prob = pi == 0 ? first_prob : 1 - first_prob;
            const int mt = tt % C::MT, nt = tt / C::MT;
            int prev = 0;
            auto kstep = [&](auto first) {
                mbar_wait(bar_full + 8 * s, ph);
                const uint32_t st = sb + s * C::STAGE;
                const uint64_t dA = mkdesc(st + wg * (64 * MB * 128), 16, 1024, 1);
                const uint64_t dB = mkdesc(st + C::A_BYTES, 8192, 1024, 1);
                wg_fence();
#pragma unroll
                for (int kk = 0; kk < 4; kk++) {
#pragma unroll
                    for (int mb = 0; mb < MB; mb++) {
                        if (decltype(first)::value && kk == 0) wg_ss192_z(acc[mb], dA + mb * 512 + kk * 2, dB + kk * 128);
                        else wg_ss192(acc[mb], dA + mb * 512 + kk * 2, dB + kk * 128);
                    }
                }
                wg_commit();
                if (!decltype(first)::value) {
                    wg_wait<1>();
                    if (lane == 0) mbar_arrive(bar_empty + 8 * prev);
                }
                prev = s;
                if (++s == STAGES) { s = 0; ph ^= 1; }
            };
            kstep(TrueT{});
#pragma unroll 1
            for (int kt = 1; kt < 16; kt++) kstep(FalseT{});
            wg_wait<0>();
            if (lane == 0) mbar_arrive(bar_empty + 8 * prev);
#pragma unroll
            for (int mb = 0; mb < MB; mb++) fence_regs<96>(acc[mb]);

            uint32_t tidl;
            asm volatile("mov.u32 %0, %%tid.x;" : "=r"(tidl));
            const int warp = (tidl >> 5) & 3, lane = tidl & 31, wg = tidl >> 7;
            const uint32_t stg = sb + C::OFF_STG + wg * 24576;
            const int strow = warp * 16 + (lane & 7) + ((lane >> 3) & 1) * 8;
            const uint32_t st_base = stg + strow * 64;
            const uint32_t st_x = (strow >> 1) & 3, st_c = lane >> 4;
            if (prob == 0) { mbar_wait(bar_phi_full, phi_ph); phi_ph ^= 1; }
#pragma unroll
            for (int mb = 0; mb < MB; mb++) {
                const int tok0 = mt * C::BM + wg * (64 * MB) + mb * 64;
                float* a = acc[mb];
                if (stores_pending) {
                    if (warp == 0 && lane == 0) bulk_wait_read<0>();
                    bar_sync(1 + wg, 128);
                }
                auto stage_block = [&](int sbk, const uint32_t* pk) {
                    stsm_x4(st_base + sbk * 4096 + ((st_c ^ st_x) << 4), pk[0], pk[1], pk[2], pk[3]);
                    stsm_x4(st_base + sbk * 4096 + (((2 + st_c) ^ st_x) << 4), pk[4], pk[5], pk[6], pk[7]);
                };
                if (prob == 1) {
#pragma unroll
                    for (int p = 0; p < 3; p++) {
#pragma unroll
                        for (int hh = 0; hh < 2; hh++) {
                            float s0 = 0.f, s1 = 0.f;
                            uint32_t pk[8];
#pragma unroll
                            for (int g = 0; g < 4; g++) {
                                const int j = p * 8 + hh * 4 + g;
                                float v0 = a[4 * j], v1 = a[4 * j + 1], v2 = a[4 * j + 2], v3 = a[4 * j + 3];
                                if (p == 0) { v0 *= QSCALE; v1 *= QSCALE; v2 *= QSCALE; v3 *= QSCALE; }
                                s0 = fmaf(v0, v0, s0); s0 = fmaf(v1, v1, s0);
                                s1 = fmaf(v2, v2, s1); s1 = fmaf(v3, v3, s1);
                                pk[2 * g] = pack_bf16(v0, v1); pk[2 * g + 1] = pack_bf16(v2, v3);
                            }
                            stage_block(p * 2 + hh, pk);
                            s0 += __shfl_xor_sync(0xffffffffu, s0, 1); s1 += __shfl_xor_sync(0xffffffffu, s1, 1);
                            s0 += __shfl_xor_sync(0xffffffffu, s0, 2); s1 += __shfl_xor_sync(0xffffffffu, s1, 2);
                            float m = (s0 > s1 || s0 != s0) ? s0 : s1;
#pragma unroll
                            for (int o = 4; o < 32; o <<= 1) {
                                float m2 = __shfl_xor_sync(0xffffffffu, m, o);
                                m = (m2 > m || m2 != m2) ? m2 : m;
                            }
                            if (lane == 0) g_norm[(p * NH + nt * 2 + hh) * 128 + (tok0 >> 4) + warp] = m;
                        }
                    }
                } else {
#pragma unroll
                    for (int hh = 0; hh < 2; hh++) {
                        uint32_t pk[8];
#pragma unroll
                        for (int g = 0; g < 4; g++) {
                            const int j = 16 + hh * 4 + g;
                            pk[2 * g] = pack_bf16(a[4 * j], a[4 * j + 1]); pk[2 * g + 1] = pack_bf16(a[4 * j + 2], a[4 * j + 3]);
                        }
                        stage_block(4 + hh, pk);
                    }
#pragma unroll
                    for (int p = 0; p < 2; p++) {
                        uint32_t fr[16];
                        float f[2][16];
#pragma unroll
                        for (int j = 0; j < 8; j++) {
                            const int jj = p * 8 + j;
                            fr[2 * j] = pack_bf16(a[4 * jj], a[4 * jj + 1]); fr[2 * j + 1] = pack_bf16(a[4 * jj + 2], a[4 * jj + 3]);
                        }
                        fence_regs_u<16>(fr);
                        wg_fence();
#pragma unroll
                        for (int hh = 0; hh < 2; hh++) {
                            const uint64_t dP = mkdesc(sb + C::OFF_PHI + hh * 2048, 16, 512, 2);
                            wg_rs32t_z(f[hh], fr[8 * hh], fr[8 * hh + 1], fr[8 * hh + 2], fr[8 * hh + 3], dP);
                            wg_rs32t(f[hh], fr[8 * hh + 4], fr[8 * hh + 5], fr[8 * hh + 6], fr[8 * hh + 7], dP + 64);
                        }
                        wg_commit();
                        wg_wait<0>();
                        fence_regs<16>(f[0]); fence_regs<16>(f[1]);
#pragma unroll
                        for (int hh = 0; hh < 2; hh++) {
                            uint32_t pk[8];
#pragma unroll
                            for (int g = 0; g < 4; g++) {
                                pk[2 * g] = pack_bf16(f[hh][4 * g], f[hh][4 * g + 1]); pk[2 * g + 1] = pack_bf16(f[hh][4 * g + 2], f[hh][4 * g + 3]);
                            }
                            stage_block(p * 2 + hh, pk);
                        }
                    }
                    if (mb == MB - 1 && lane == 0) mbar_arrive(bar_phi_empty);
                }
                fence_async_smem();
                bar_sync(1 + wg, 128);
                if (warp == 0 && lane == 0) {
#pragma unroll
                    for (int sbk = 0; sbk < 6; sbk++) {
                        const int p = sbk >> 1, hh = sbk & 1;
                        tma_store(&tm.qkv64, stg + sbk * 4096, 0, ((prob * 3 + p) * NH + nt * 2 + hh) * SEQ + tok0);
                    }
                    bulk_commit();
                }
                stores_pending = true;
            }
        }
        if (warp == 0 && lane == 0) bulk_wait<0>();
    }
}

template <int BN, int STAGES> struct OutCfg {
    static constexpr int A_BYTES = 128 * 128;
    static constexpr int B_BYTES = (BN / 64) * 8192;
    static constexpr int STAGE = A_BYTES + B_BYTES;
    static constexpr int OFF_BAR = STAGES * STAGE;
    static constexpr int SMEM = OFF_BAR + 128 + 1024;
    static constexpr int NT = DM / BN;
};

template <int BN> __device__ __forceinline__ void wg_ss_z(float* d, uint64_t a, uint64_t b);
template <> __device__ __forceinline__ void wg_ss_z<128>(float* d, uint64_t a, uint64_t b) { wg_ss128_z(d, a, b); }
template <> __device__ __forceinline__ void wg_ss_z<256>(float* d, uint64_t a, uint64_t b) { wg_ss256_z(d, a, b); }
template <int BN> __device__ __forceinline__ void wg_ss(float* d, uint64_t a, uint64_t b);
template <> __device__ __forceinline__ void wg_ss<128>(float* d, uint64_t a, uint64_t b) { wg_ss128(d, a, b); }
template <> __device__ __forceinline__ void wg_ss<256>(float* d, uint64_t a, uint64_t b) { wg_ss256(d, a, b); }

template <int BN, int STAGES, int RC, int RP>
__global__ void __launch_bounds__(384, 1)
out_gemm_kernel(const __grid_constant__ TMaps tm, int prob_begin) {
    using C = OutCfg<BN, STAGES>;
    extern __shared__ uint8_t smem_raw[];
    const uint32_t sb = (smem_u32(smem_raw) + 1023) & ~1023u;
    const uint32_t bar_full = sb + C::OFF_BAR, bar_empty = bar_full + 8 * STAGES;
    const int wg = threadIdx.x >> 7;
    const int warp = (threadIdx.x >> 5) & 3, lane = threadIdx.x & 31;
    const int t = blockIdx.x;
    const int prob = prob_begin + t / (16 * C::NT);
    const int mt = (t % (16 * C::NT)) % 16, nt = (t % (16 * C::NT)) / 16;

    if (threadIdx.x == 0) {
        for (int s = 0; s < STAGES; s++) { mbar_init(bar_full + 8 * s, 1); mbar_init(bar_empty + 8 * s, 8); }
        fence_mbar_init();
    }
    __syncthreads();

    if (wg == 2) {
        reg_dec<RP>();
        if (warp == 0 && lane == 0) {
            const CUtensorMap* mw = &tm.wo[prob];
            prefetch_tmap(mw); prefetch_tmap(&tm.o); prefetch_tmap(&tm.out);
#pragma unroll
            for (int s = 0; s < STAGES; s++) {
                const uint32_t st = sb + s * C::STAGE, fb = bar_full + 8 * s;
                mbar_expect_tx(fb, C::STAGE);
#pragma unroll
                for (int p = 0; p < BN / 64; p++) tma_load(st + C::A_BYTES + p * 8192, mw, fb, nt * BN + p * 64, s * 64);
            }
            pdl_wait();
#pragma unroll
            for (int s = 0; s < STAGES; s++) tma_load(sb + s * C::STAGE, &tm.o, bar_full + 8 * s, s * 64, prob * SEQ + mt * 128);
            int s = 0; uint32_t ph = 0;
            for (int kt = STAGES; kt < 16; kt++) {
                mbar_wait(bar_empty + 8 * s, ph);
                const uint32_t st = sb + s * C::STAGE, fb = bar_full + 8 * s;
                mbar_expect_tx(fb, C::STAGE);
                tma_load(st, &tm.o, fb, kt * 64, prob * SEQ + mt * 128);
#pragma unroll
                for (int p = 0; p < BN / 64; p++) tma_load(st + C::A_BYTES + p * 8192, mw, fb, nt * BN + p * 64, kt * 64);
                if (++s == STAGES) { s = 0; ph ^= 1; }
            }
        }
    } else {
        reg_inc<RC>();
        float acc[BN / 2];
        int s = 0; uint32_t ph = 0; int prev = 0;
        auto kstep = [&](auto first) {
            mbar_wait(bar_full + 8 * s, ph);
            const uint32_t st = sb + s * C::STAGE;
            const uint64_t dA = mkdesc(st + wg * (64 * 128), 16, 1024, 1);
            const uint64_t dB = mkdesc(st + C::A_BYTES, 8192, 1024, 1);
            wg_fence();
#pragma unroll
            for (int kk = 0; kk < 4; kk++) {
                if (decltype(first)::value && kk == 0) wg_ss_z<BN>(acc, dA + kk * 2, dB + kk * 128);
                else wg_ss<BN>(acc, dA + kk * 2, dB + kk * 128);
            }
            wg_commit();
            if (!decltype(first)::value) {
                wg_wait<1>();
                if (lane == 0) mbar_arrive(bar_empty + 8 * prev);
            }
            prev = s;
            if (++s == STAGES) { s = 0; ph ^= 1; }
        };
        kstep(TrueT{});
#pragma unroll 1
        for (int kt = 1; kt < 16; kt++) kstep(FalseT{});
        wg_wait<0>();
        fence_regs<BN / 2>(acc);
        bar_sync(3, 256);
        const uint32_t stg = sb + wg * (BN / 64) * 8192;
        const int strow = warp * 16 + (lane & 7) + ((lane >> 3) & 1) * 8;
        const uint32_t st_base = stg + strow * 128;
        const uint32_t st_x = strow & 7, st_c = lane >> 4;
#pragma unroll
        for (int b = 0; b < BN / 64; b++) {
#pragma unroll
            for (int jj = 0; jj < 4; jj++) {
                const int j = b * 8 + jj * 2;
                stsm_x4(st_base + b * 8192 + (((jj * 2 + st_c) ^ st_x) << 4),
                        pack_bf16(acc[4 * j], acc[4 * j + 1]), pack_bf16(acc[4 * j + 2], acc[4 * j + 3]),
                        pack_bf16(acc[4 * j + 4], acc[4 * j + 5]), pack_bf16(acc[4 * j + 6], acc[4 * j + 7]));
            }
        }
        fence_async_smem();
        bar_sync(1 + wg, 128);
        if (warp == 0 && lane == 0) {
#pragma unroll
            for (int b = 0; b < BN / 64; b++) tma_store(&tm.out, stg + b * 8192, prob * DM + nt * BN + b * 64, mt * 128 + wg * 64);
            bulk_commit();
            bulk_wait<0>();
        }
    }
}

template <int MASK16, int N> __device__ __forceinline__ void exp_pack(const float* s, uint32_t* p) {
#pragma unroll
    for (int i = 0; i < N / 2; i++) {
        float a = s[2 * i], b = s[2 * i + 1];
        a = ((MASK16 >> ((2 * i) & 15)) & 1) ? ex2_poly(a) : ex2(a);
        b = ((MASK16 >> ((2 * i + 1) & 15)) & 1) ? ex2_poly(b) : ex2(b);
        p[i] = pack_bf16(a, b);
    }
}

template <int NWG, int KVST> struct AttCfg {
    static constexpr int THREADS = NWG * 128;
    static constexpr int QROWS = NWG * 64;
    static constexpr int KV_STAGE = 16384;
    static constexpr int OFF_Q = KVST * KV_STAGE;
    static constexpr int OFF_ONES = OFF_Q + 2 * QROWS * 64;
    static constexpr int OFF_BAR = OFF_ONES + 1024;
    static constexpr int SMEM = OFF_BAR + 256 + 1024;
    static constexpr int NTASK = NH * (SEQ / QROWS);
};

constexpr float SAFE_BOUND = 60.0f;

template <int NWG, int KVST, int MASK16, int PP>
__global__ void __launch_bounds__(NWG * 128, 1)
attn_kernel(const __grid_constant__ TMaps tm) {
    using C = AttCfg<NWG, KVST>;
    extern __shared__ uint8_t smem_raw[];
    const uint32_t sb = (smem_u32(smem_raw) + 1023) & ~1023u;
    const uint32_t bar_full = sb + C::OFF_BAR, bar_empty = bar_full + 8 * KVST;
    const uint32_t bar_qfull = bar_empty + 8 * KVST, bar_qempty = bar_qfull + 16;
    const int wg = threadIdx.x >> 7;
    const int warp = (threadIdx.x >> 5) & 3, lane = threadIdx.x & 31;

    if (threadIdx.x == 0) {
        for (int s = 0; s < KVST; s++) { mbar_init(bar_full + 8 * s, 1); mbar_init(bar_empty + 8 * s, NWG * 4); }
        for (int s = 0; s < 2; s++) { mbar_init(bar_qfull + 8 * s, 1); mbar_init(bar_qempty + 8 * s, NWG * 4); }
        fence_mbar_init();
    }
    if (threadIdx.x < 64) {
        asm volatile("st.shared.v4.b32 [%0], {%1, %2, %2, %2};" ::"r"(sb + C::OFF_ONES + threadIdx.x * 16), "r"(0x00003F80u), "r"(0u) : "memory");
        fence_async_smem();
    }
    __syncthreads();
    pdl_launch();
    pdl_wait();

    struct Producer {
        int s = 0; uint32_t ph = 1; int qs = 0; uint32_t qph = 1;
        int t, st = 0;
    } pr;
    pr.t = blockIdx.x;
    auto produce = [&]() {
        if (pr.t >= C::NTASK) return;
        const int h = pr.t / (SEQ / C::QROWS), qt = pr.t % (SEQ / C::QROWS);
        if (pr.st == 0) {
            mbar_wait(bar_qempty + 8 * pr.qs, pr.qph);
            mbar_expect_tx(bar_qfull + 8 * pr.qs, C::QROWS * 64);
            const int rowQ = ((3 + 0) * NH + h) * SEQ + qt * C::QROWS;
#pragma unroll
            for (int i = 0; i < C::QROWS / 128; i++)
                tma_load(sb + C::OFF_Q + pr.qs * C::QROWS * 64 + i * 8192, &tm.qkv128, bar_qfull + 8 * pr.qs, 0, rowQ + i * 128);
            if (++pr.qs == 2) { pr.qs = 0; pr.qph ^= 1; }
        }
        mbar_wait(bar_empty + 8 * pr.s, pr.ph);
        const uint32_t dst = sb + pr.s * C::KV_STAGE, fb = bar_full + 8 * pr.s;
        mbar_expect_tx(fb, C::KV_STAGE);
        tma_load(dst, &tm.qkv128, fb, 0, ((3 + 1) * NH + h) * SEQ + pr.st * 128);
        tma_load(dst + 8192, &tm.qkv128, fb, 0, ((3 + 2) * NH + h) * SEQ + pr.st * 128);
        if (++pr.s == KVST) { pr.s = 0; pr.ph ^= 1; }
        if (++pr.st == 16) { pr.st = 0; pr.t += gridDim.x; }
    };
    if (threadIdx.x == 0) {
        prefetch_tmap(&tm.qkv128);
#pragma unroll 1
        for (int i = 0; i < KVST - 1; i++) produce();
    }
    __syncwarp();
    {
        int s = 0; uint32_t ph = 0; int qs = 0; uint32_t qph = 0;
        const int mybar = 1 + wg, nextbar = 1 + (wg + 1) % NWG;
        if (PP && wg == NWG - 1) bar_arrive(1, 256);
        const int qrow = wg * 64 + warp * 16 + (lane & 7) + ((lane >> 3) & 1) * 8;
        const uint64_t DV_STEP = (uint64_t)64 - ((uint64_t)64 << 16);
        for (int t = blockIdx.x; t < C::NTASK; t += gridDim.x) {
            const int h = t / (SEQ / C::QROWS), qt = t % (SEQ / C::QROWS);
            bool fast;
            {
                float qm = 0.f, km = 0.f, vm = 0.f;
                bool bad = false;
#pragma unroll
                for (int i = 0; i < 4; i++) {
                    float a = g_norm[(0 * NH + h) * 128 + lane + 32 * i], b = g_norm[(1 * NH + h) * 128 + lane + 32 * i], c = g_norm[(2 * NH + h) * 128 + lane + 32 * i];
                    bad |= !(a < 1e30f) || !(b < 1e30f) || !(c < 1e30f);
                    qm = fmaxf(qm, a); km = fmaxf(km, b); vm = fmaxf(vm, c);
                }
#pragma unroll
                for (int o = 1; o < 32; o <<= 1) {
                    qm = fmaxf(qm, __shfl_xor_sync(0xffffffffu, qm, o));
                    km = fmaxf(km, __shfl_xor_sync(0xffffffffu, km, o));
                    vm = fmaxf(vm, __shfl_xor_sync(0xffffffffu, vm, o));
                }
                fast = __all_sync(0xffffffffu, !bad && (qm * km * 1.05f <= SAFE_BOUND * SAFE_BOUND) && (vm <= 1e24f) && (vm >= 1e-20f));
            }
            uint32_t q[8];
            mbar_wait(bar_qfull + 8 * qs, qph);
            {
                const uint32_t qa = sb + C::OFF_Q + qs * C::QROWS * 64 + qrow * 64;
                const uint32_t x = (qrow >> 1) & 3, c = lane >> 4;
                ldsm_x4(qa + (((0 + c) ^ x) << 4), q[0], q[1], q[2], q[3]);
                ldsm_x4(qa + (((2 + c) ^ x) << 4), q[4], q[5], q[6], q[7]);
            }
            fence_regs_u<8>(q);
            __syncwarp();
            if (lane == 0) mbar_arrive(bar_qempty + 8 * qs);
            if (++qs == 2) { qs = 0; qph ^= 1; }

            float o[20];
#pragma unroll
            for (int i = 0; i < 20; i++) o[i] = 0.f;
            fence_regs<20>(o);
            float sc[32];
            uint32_t p[16];

            if (fast) {
                auto step = [&](uint64_t dVb, uint64_t dKb) {
                    if (PP) bar_sync(mybar, 256);
                    wg_fence();
#pragma unroll
                    for (int kk = 0; kk < 4; kk++) wg_rs40t(o, p[4 * kk], p[4 * kk + 1], p[4 * kk + 2], p[4 * kk + 3], dVb + kk * DV_STEP);
                    wg_rs64_z(sc, q[0], q[1], q[2], q[3], dKb);
                    wg_rs64(sc, q[4], q[5], q[6], q[7], dKb + 2);
                    wg_commit();
                    if (PP) bar_arrive(nextbar, 256);
                    wg_wait<0>();
                    fence_regs<32>(sc); fence_regs<20>(o);
                };
                mbar_wait(bar_full + 8 * s, ph);
                uint32_t kb = sb + s * C::KV_STAGE;
                if (PP) bar_sync(mybar, 256);
                wg_fence();
                wg_rs64_z(sc, q[0], q[1], q[2], q[3], mkdesc(kb, 16, 512, 2));
                wg_rs64(sc, q[4], q[5], q[6], q[7], mkdesc(kb, 16, 512, 2) + 2);
                wg_commit();
                if (PP) bar_arrive(nextbar, 256);
                wg_wait<0>();
                fence_regs<32>(sc);
                exp_pack<MASK16, 32>(sc, p);
#pragma unroll 1
                for (int st = 0; st < 15; st++) {
                    const uint64_t dK = mkdesc(kb, 16, 512, 2);
                    const uint64_t dV = mkdesc(kb + 8192, sb + C::OFF_ONES - (kb + 8192), 512, 2);
                    step(dV, dK + 256);
                    if (threadIdx.x == 0) produce();
                    __syncwarp();
                    exp_pack<MASK16, 32>(sc, p);
                    const int scur = s;
                    if (++s == KVST) { s = 0; ph ^= 1; }
                    mbar_wait(bar_full + 8 * s, ph);
                    kb = sb + s * C::KV_STAGE;
                    step(dV + 4 * DV_STEP, mkdesc(kb, 16, 512, 2));
                    if (lane == 0) mbar_arrive(bar_empty + 8 * scur);
                    exp_pack<MASK16, 32>(sc, p);
                }
                {
                    const uint64_t dK = mkdesc(kb, 16, 512, 2);
                    const uint64_t dV = mkdesc(kb + 8192, sb + C::OFF_ONES - (kb + 8192), 512, 2);
                    step(dV, dK + 256);
                    if (threadIdx.x == 0) produce();
                    __syncwarp();
                    exp_pack<MASK16, 32>(sc, p);
                    wg_fence();
#pragma unroll
                    for (int kk = 0; kk < 4; kk++) wg_rs40t(o, p[4 * kk], p[4 * kk + 1], p[4 * kk + 2], p[4 * kk + 3], dV + (4 + kk) * DV_STEP);
                    wg_commit();
                    wg_wait<0>();
                    fence_regs<20>(o);
                    if (lane == 0) mbar_arrive(bar_empty + 8 * s);
                    if (++s == KVST) { s = 0; ph ^= 1; }
                }
            } else {
                float m0 = -INFINITY, m1 = -INFINITY;
#pragma unroll 1
                for (int st = 0; st < 16; st++) {
                    mbar_wait(bar_full + 8 * s, ph);
                    const uint32_t kb = sb + s * C::KV_STAGE;
                    const uint64_t dK = mkdesc(kb, 16, 512, 2);
                    const uint64_t dV = mkdesc(kb + 8192, sb + C::OFF_ONES - (kb + 8192), 512, 2);
#pragma unroll 1
                    for (int sub = 0; sub < 2; sub++) {
                        wg_fence();
                        wg_rs64_z(sc, q[0], q[1], q[2], q[3], dK + sub * 256);
                        wg_rs64(sc, q[4], q[5], q[6], q[7], dK + sub * 256 + 2);
                        wg_commit();
                        wg_wait<0>();
                        fence_regs<32>(sc);
                        float x0 = m0, x1 = m1;
#pragma unroll
                        for (int j = 0; j < 8; j++) {
                            x0 = fmaxf(x0, fmaxf(sc[4 * j], sc[4 * j + 1]));
                            x1 = fmaxf(x1, fmaxf(sc[4 * j + 2], sc[4 * j + 3]));
                        }
                        x0 = fmaxf(x0, __shfl_xor_sync(0xffffffffu, x0, 1)); x0 = fmaxf(x0, __shfl_xor_sync(0xffffffffu, x0, 2));
                        x1 = fmaxf(x1, __shfl_xor_sync(0xffffffffu, x1, 1)); x1 = fmaxf(x1, __shfl_xor_sync(0xffffffffu, x1, 2));
                        const float al0 = ex2(m0 - x0), al1 = ex2(m1 - x1);
                        m0 = x0; m1 = x1;
#pragma unroll
                        for (int j = 0; j < 5; j++) { o[4 * j] *= al0; o[4 * j + 1] *= al0; o[4 * j + 2] *= al1; o[4 * j + 3] *= al1; }
#pragma unroll
                        for (int j = 0; j < 8; j++) {
                            p[2 * j] = pack_bf16(ex2(sc[4 * j] - x0), ex2(sc[4 * j + 1] - x0));
                            p[2 * j + 1] = pack_bf16(ex2(sc[4 * j + 2] - x1), ex2(sc[4 * j + 3] - x1));
                        }
                        fence_regs<20>(o); fence_regs_u<16>(p);
                        wg_fence();
#pragma unroll
                        for (int kk = 0; kk < 4; kk++) wg_rs40t(o, p[4 * kk], p[4 * kk + 1], p[4 * kk + 2], p[4 * kk + 3], dV + (sub * 4 + kk) * DV_STEP);
                        wg_commit();
                        wg_wait<0>();
                        fence_regs<20>(o);
                    }
                    if (lane == 0) mbar_arrive(bar_empty + 8 * s);
                    if (threadIdx.x == 0) produce();
                    __syncwarp();
                    if (++s == KVST) { s = 0; ph ^= 1; }
                }
            }
            const float l0 = __shfl_sync(0xffffffffu, o[16], lane & ~3), l1 = __shfl_sync(0xffffffffu, o[18], lane & ~3);
            const float i0 = 1.0f / l0, i1 = 1.0f / l1;
            const int tok = qt * C::QROWS + wg * 64 + warp * 16 + (lane >> 2);
            uint32_t* dst = reinterpret_cast<uint32_t*>(g_o + (size_t)(SEQ + tok) * DM + h * 32 + (lane & 3) * 2);
#pragma unroll
            for (int j = 0; j < 4; j++) {
                dst[j * 4] = pack_bf16(o[4 * j] * i0, o[4 * j + 1] * i0);
                dst[j * 4 + 8 * (DM / 2)] = pack_bf16(o[4 * j + 2] * i1, o[4 * j + 3] * i1);
            }
        }
        if (PP && wg == 0) bar_sync(1, 256);
    }
}

__device__ __forceinline__ void hedgehog_row(const uint4 raw, uint32_t* pos, uint32_t* neg) {
    float x[8];
    const uint32_t w[4] = {raw.x, raw.y, raw.z, raw.w};
#pragma unroll
    for (int i = 0; i < 4; i++) { x[2 * i] = __uint_as_float(w[i] << 16); x[2 * i + 1] = __uint_as_float(w[i] & 0xffff0000u); }
    float mx = x[0], mn = x[0];
#pragma unroll
    for (int i = 1; i < 8; i++) { mx = fmaxf(mx, x[i]); mn = fminf(mn, x[i]); }
    mx = fmaxf(mx, __shfl_xor_sync(0xffffffffu, mx, 1)); mn = fminf(mn, __shfl_xor_sync(0xffffffffu, mn, 1));
    mx = fmaxf(mx, __shfl_xor_sync(0xffffffffu, mx, 2)); mn = fminf(mn, __shfl_xor_sync(0xffffffffu, mn, 2));
    constexpr float L2E = 1.4426950408889634f;
    const float mxs = -mx * L2E, mns = mn * L2E;
    float ep[8], en[8], sp = 0.f, sn = 0.f;
#pragma unroll
    for (int i = 0; i < 8; i++) {
        ep[i] = ex2(fmaf(x[i], L2E, mxs));
        en[i] = ex2(fmaf(x[i], -L2E, mns));
        sp += ep[i]; sn += en[i];
    }
    sp += __shfl_xor_sync(0xffffffffu, sp, 1); sn += __shfl_xor_sync(0xffffffffu, sn, 1);
    sp += __shfl_xor_sync(0xffffffffu, sp, 2); sn += __shfl_xor_sync(0xffffffffu, sn, 2);
    const float ip = 1.0f / sp, in = 1.0f / sn;
#pragma unroll
    for (int i = 0; i < 4; i++) {
        pos[i] = pack_bf16(ep[2 * i] * ip, ep[2 * i + 1] * ip);
        neg[i] = pack_bf16(en[2 * i] * in, en[2 * i + 1] * in);
    }
}

__global__ void __launch_bounds__(128) lin_kv_kernel() {
    __shared__ __align__(1024) uint8_t sm[8192 + 4096 + 1024];
    const uint32_t sphi = smem_u32(sm), sv = sphi + 8192, sones = sv + 4096;
    const int h = blockIdx.x >> 3, ch = blockIdx.x & 7;
    const int warp = threadIdx.x >> 5, lane = threadIdx.x & 31;
    const int r = lane >> 2, c = lane & 3;
    if (threadIdx.x < 64) asm volatile("st.shared.v4.b32 [%0], {%1, %2, %2, %2};" ::"r"(sones + threadIdx.x * 16), "r"(0x00003F80u), "r"(0u) : "memory");
    pdl_launch();
    pdl_wait();
    const __nv_bfloat16* gk = g_qkv + (size_t)((0 * 3 + 1) * NH + h) * SEQ * 32;
    const __nv_bfloat16* gv = g_qkv + (size_t)((0 * 3 + 2) * NH + h) * SEQ * 32;
    float acc[20];
#pragma unroll
    for (int i = 0; i < 20; i++) acc[i] = 0.f;
    fence_regs<20>(acc);
    const uint64_t dA = mkdesc(sphi, 16, 1024, 1);
    const uint64_t dB = mkdesc(sv, sones - sv, 512, 2);
    const uint64_t DV_STEP = (uint64_t)64 - ((uint64_t)64 << 16);
#pragma unroll 1
    for (int mb = 0; mb < 4; mb++) {
        const int tok0 = ch * 256 + mb * 64;
        const int row0 = warp * 16 + r;
        const uint4 k0 = *reinterpret_cast<const uint4*>(gk + (size_t)(tok0 + row0) * 32 + c * 8);
        const uint4 k1 = *reinterpret_cast<const uint4*>(gk + (size_t)(tok0 + row0 + 8) * 32 + c * 8);
        uint4 vv[2];
#pragma unroll
        for (int i = 0; i < 2; i++) {
            const int idx = threadIdx.x + 128 * i;
            vv[i] = *reinterpret_cast<const uint4*>(gv + (size_t)tok0 * 32 + idx * 8);
        }
        uint32_t pos0[4], neg0[4], pos1[4], neg1[4];
        hedgehog_row(k0, pos0, neg0);
        hedgehog_row(k1, pos1, neg1);
        if (mb > 0) __syncthreads();
        {
            const int ra = row0, rb = row0 + 8;
            asm volatile("st.shared.v4.b32 [%0], {%1, %2, %3, %4};" ::"r"(sphi + ra * 128 + ((c ^ (ra & 7)) << 4)), "r"(pos0[0]), "r"(pos0[1]), "r"(pos0[2]), "r"(pos0[3]) : "memory");
            asm volatile("st.shared.v4.b32 [%0], {%1, %2, %3, %4};" ::"r"(sphi + ra * 128 + (((4 + c) ^ (ra & 7)) << 4)), "r"(neg0[0]), "r"(neg0[1]), "r"(neg0[2]), "r"(neg0[3]) : "memory");
            asm volatile("st.shared.v4.b32 [%0], {%1, %2, %3, %4};" ::"r"(sphi + rb * 128 + ((c ^ (rb & 7)) << 4)), "r"(pos1[0]), "r"(pos1[1]), "r"(pos1[2]), "r"(pos1[3]) : "memory");
            asm volatile("st.shared.v4.b32 [%0], {%1, %2, %3, %4};" ::"r"(sphi + rb * 128 + (((4 + c) ^ (rb & 7)) << 4)), "r"(neg1[0]), "r"(neg1[1]), "r"(neg1[2]), "r"(neg1[3]) : "memory");
#pragma unroll
            for (int i = 0; i < 2; i++) {
                const int idx = threadIdx.x + 128 * i, vr = idx >> 2, vc = idx & 3;
                asm volatile("st.shared.v4.b32 [%0], {%1, %2, %3, %4};" ::"r"(sv + vr * 64 + ((vc ^ ((vr >> 1) & 3)) << 4)), "r"(vv[i].x), "r"(vv[i].y), "r"(vv[i].z), "r"(vv[i].w) : "memory");
            }
        }
        fence_async_smem();
        __syncthreads();
        wg_fence();
#pragma unroll
        for (int kk = 0; kk < 4; kk++) wg_ss40tt(acc, dA + kk * 128, dB + kk * DV_STEP);
        wg_commit();
        wg_wait<0>();
        fence_regs<20>(acc);
    }
    float* dst = g_kvp + (size_t)(h * 8 + ch) * 2560 + (warp * 16 + r) * 40 + c * 2;
#pragma unroll
    for (int j = 0; j < 5; j++) {
        *reinterpret_cast<float2*>(dst + j * 8) = make_float2(acc[4 * j], acc[4 * j + 1]);
        *reinterpret_cast<float2*>(dst + 8 * 40 + j * 8) = make_float2(acc[4 * j + 2], acc[4 * j + 3]);
    }
}

__global__ void __launch_bounds__(128) lin_out_kernel() {
    __shared__ __align__(1024) uint8_t sm[8192];
    const uint32_t skv = smem_u32(sm);
    const int h = blockIdx.x >> 3, ch = blockIdx.x & 7;
    const int warp = threadIdx.x >> 5, lane = threadIdx.x & 31;
    const int r = lane >> 2, c = lane & 3;
    pdl_launch();
    pdl_wait();
    for (int idx = threadIdx.x; idx < 320; idx += 128) {
        const int f = idx / 5, cg = idx % 5;
        float sum[8];
#pragma unroll
        for (int i = 0; i < 8; i++) sum[i] = 0.f;
#pragma unroll
        for (int pp = 0; pp < 8; pp++) {
            const float4* src = reinterpret_cast<const float4*>(g_kvp + (size_t)(h * 8 + pp) * 2560 + f * 40 + cg * 8);
            const float4 a = src[0], b = src[1];
            sum[0] += a.x; sum[1] += a.y; sum[2] += a.z; sum[3] += a.w; sum[4] += b.x; sum[5] += b.y; sum[6] += b.z; sum[7] += b.w;
        }
        const int half = f >> 5, cc = (f >> 3) & 3, i = f & 7;
        const int kp = half * 32 + 16 * (i >> 2) + 8 * ((i >> 1) & 1) + 2 * cc + (i & 1);
        const uint32_t a = skv + (cg == 4 ? 4096 : 0) + kp * 64 + (((cg & 3) ^ ((kp >> 1) & 3)) << 4);
        asm volatile("st.shared.v4.b32 [%0], {%1, %2, %3, %4};" ::"r"(a), "r"(pack_bf16(sum[0], sum[1])), "r"(pack_bf16(sum[2], sum[3])),
                     "r"(pack_bf16(sum[4], sum[5])), "r"(pack_bf16(sum[6], sum[7])) : "memory");
    }
    fence_async_smem();
    __syncthreads();
    const __nv_bfloat16* gq = g_qkv + (size_t)((0 * 3 + 0) * NH + h) * SEQ * 32;
    const uint64_t dB = mkdesc(skv, 4096, 512, 2);
#pragma unroll 1
    for (int mb = 0; mb < 4; mb++) {
        const int tok = ch * 256 + mb * 64 + warp * 16 + r;
        const uint4 q0 = *reinterpret_cast<const uint4*>(gq + (size_t)tok * 32 + c * 8);
        const uint4 q1 = *reinterpret_cast<const uint4*>(gq + (size_t)(tok + 8) * 32 + c * 8);
        uint32_t pos0[4], neg0[4], pos1[4], neg1[4];
        hedgehog_row(q0, pos0, neg0);
        hedgehog_row(q1, pos1, neg1);
        float acc[20];
        fence_regs_u<4>(pos0); fence_regs_u<4>(pos1); fence_regs_u<4>(neg0); fence_regs_u<4>(neg1);
        wg_fence();
        wg_rs40t_z(acc, pos0[0], pos1[0], pos0[1], pos1[1], dB);
        wg_rs40t(acc, pos0[2], pos1[2], pos0[3], pos1[3], dB + 64);
        wg_rs40t(acc, neg0[0], neg1[0], neg0[1], neg1[1], dB + 128);
        wg_rs40t(acc, neg0[2], neg1[2], neg0[3], neg1[3], dB + 192);
        wg_commit();
        wg_wait<0>();
        fence_regs<20>(acc);
        const float d0 = __shfl_sync(0xffffffffu, acc[16], lane & ~3) + 1e-6f, d1 = __shfl_sync(0xffffffffu, acc[18], lane & ~3) + 1e-6f;
        const float i0 = 1.0f / d0, i1 = 1.0f / d1;
        uint32_t* dst = reinterpret_cast<uint32_t*>(g_o + (size_t)tok * DM + h * 32 + c * 2);
#pragma unroll
        for (int j = 0; j < 4; j++) {
            dst[j * 4] = pack_bf16(acc[4 * j] * i0, acc[4 * j + 1] * i0);
            dst[j * 4 + 8 * (DM / 2)] = pack_bf16(acc[4 * j + 2] * i1, acc[4 * j + 3] * i1);
        }
    }
}

typedef CUresult (*EncodeFn)(CUtensorMap*, CUtensorMapDataType, cuuint32_t, void*, const cuuint64_t*, const cuuint64_t*,
                             const cuuint32_t*, const cuuint32_t*, CUtensorMapInterleave, CUtensorMapSwizzle,
                             CUtensorMapL2promotion, CUtensorMapFloatOOBfill);

void make_map(EncodeFn enc, CUtensorMap* m, const void* ptr, uint64_t d0, uint64_t d1, uint32_t b0, uint32_t b1, CUtensorMapSwizzle sw) {
    cuuint64_t dims[2] = {d0, d1};
    cuuint64_t strides[1] = {d0 * 2};
    cuuint32_t box[2] = {b0, b1};
    cuuint32_t es[2] = {1, 1};
    enc(m, CU_TENSOR_MAP_DATA_TYPE_BFLOAT16, 2, const_cast<void*>(ptr), dims, strides, box, es, CU_TENSOR_MAP_INTERLEAVE_NONE, sw,
        CU_TENSOR_MAP_L2_PROMOTION_L2_128B, CU_TENSOR_MAP_FLOAT_OOB_FILL_NONE);
}

template <typename... KArgs, typename... Args>
void launch(void (*k)(KArgs...), int grid, int block, int smem, cudaStream_t st, bool pdl, Args... args) {
    cudaLaunchConfig_t cfg = {};
    cfg.gridDim = dim3(grid); cfg.blockDim = dim3(block); cfg.dynamicSmemBytes = smem; cfg.stream = st;
    cudaLaunchAttribute at[1];
    at[0].id = cudaLaunchAttributeProgrammaticStreamSerialization;
    at[0].val.programmaticStreamSerializationAllowed = 1;
    cfg.attrs = at; cfg.numAttrs = pdl ? 1 : 0;
    cudaLaunchKernelEx(&cfg, k, KArgs(args)...);
}

constexpr int K1_MB = 2, K1_ST = 3;
constexpr int K3_BN = 256, K3_ST = 4;
constexpr int K2_NWG = 4, K2_KVST = 4, K2_MASK = 0x1249, K2_PP = 1;

}

extern "C" void kernel_launch(void* const* d_in, const int* in_sizes, int n_in, void* d_out, int out_size) {
    (void)in_sizes; (void)n_in; (void)out_size;
    static bool init = false;
    static TMaps tm;
    static int nsm = 132;
    static void* cached[8];
    auto k1 = qkv_gemm_kernel<K1_MB, K1_ST, 240, 24>;
    auto k2 = attn_kernel<K2_NWG, K2_KVST, K2_MASK, K2_PP>;
    auto k3 = out_gemm_kernel<K3_BN, K3_ST, 232, 40>;
    bool same = init;
    for (int i = 0; i < 7 && same; i++) same = cached[i] == d_in[i];
    same = same && cached[7] == d_out;
    if (!same) {
        void* fn = nullptr;
        cudaDriverEntryPointQueryResult qr;
        cudaGetDriverEntryPoint("cuTensorMapEncodeTiled", &fn, cudaEnableDefault, &qr);
        EncodeFn enc = (EncodeFn)fn;
        void *pqkv, *po;
        cudaGetSymbolAddress(&pqkv, g_qkv);
        cudaGetSymbolAddress(&po, g_o);
        make_map(enc, &tm.x[0], d_in[0], 1024, 2048, 64, 128 * K1_MB, CU_TENSOR_MAP_SWIZZLE_128B);
        make_map(enc, &tm.x[1], d_in[4], 1024, 2048, 64, 128 * K1_MB, CU_TENSOR_MAP_SWIZZLE_128B);
        make_map(enc, &tm.w[0], d_in[1], 3072, 1024, 64, 64, CU_TENSOR_MAP_SWIZZLE_128B);
        make_map(enc, &tm.w[1], d_in[5], 3072, 1024, 64, 64, CU_TENSOR_MAP_SWIZZLE_128B);
        make_map(enc, &tm.phi, d_in[2], 32, 1024, 32, 64, CU_TENSOR_MAP_SWIZZLE_64B);
        make_map(enc, &tm.qkv64, pqkv, 32, 2 * 3 * NH * SEQ, 32, 64, CU_TENSOR_MAP_SWIZZLE_64B);
        make_map(enc, &tm.qkv128, pqkv, 32, 2 * 3 * NH * SEQ, 32, 128, CU_TENSOR_MAP_SWIZZLE_64B);
        make_map(enc, &tm.o, po, 1024, 2 * SEQ, 64, 128, CU_TENSOR_MAP_SWIZZLE_128B);
        make_map(enc, &tm.wo[0], d_in[3], 1024, 1024, 64, 64, CU_TENSOR_MAP_SWIZZLE_128B);
        make_map(enc, &tm.wo[1], d_in[6], 1024, 1024, 64, 64, CU_TENSOR_MAP_SWIZZLE_128B);
        make_map(enc, &tm.out, d_out, 2048, 2048, 64, 64, CU_TENSOR_MAP_SWIZZLE_128B);
        cudaFuncSetAttribute(k1, cudaFuncAttributeMaxDynamicSharedMemorySize, QkvCfg<K1_MB, K1_ST>::SMEM);
        cudaFuncSetAttribute(k2, cudaFuncAttributeMaxDynamicSharedMemorySize, AttCfg<K2_NWG, K2_KVST>::SMEM);
        cudaFuncSetAttribute(k3, cudaFuncAttributeMaxDynamicSharedMemorySize, OutCfg<K3_BN, K3_ST>::SMEM);
        int dev = 0;
        cudaGetDevice(&dev);
        cudaDeviceGetAttribute(&nsm, cudaDevAttrMultiProcessorCount, dev);
        for (int i = 0; i < 7; i++) cached[i] = d_in[i];
        cached[7] = d_out;
        init = true;
    }
    cudaStream_t st = cudaStreamPerThread;
    const int ntile = 2 * QkvCfg<K1_MB, K1_ST>::TPP;
    launch(k1, ntile < nsm ? ntile : nsm, 384, QkvCfg<K1_MB, K1_ST>::SMEM, st, false, tm, 0, ntile, 1);
    launch(lin_kv_kernel, 256, 128, 0, st, true);
    launch(lin_out_kernel, 256, 128, 0, st, true);
    const int ntask = AttCfg<K2_NWG, K2_KVST>::NTASK;
    launch(k2, ntask < nsm ? ntask : nsm, AttCfg<K2_NWG, K2_KVST>::THREADS, AttCfg<K2_NWG, K2_KVST>::SMEM, st, true, tm);
    launch(k3, 2 * 16 * OutCfg<K3_BN, K3_ST>::NT, 384, OutCfg<K3_BN, K3_ST>::SMEM, st, true, tm, 0);
}
```

```cpp
#include <cuda_runtime.h>
#include <cuda_bf16.h>
#include <cuda.h>
#include <stdint.h>

namespace {

constexpr int SEQ = 2048;
constexpr int DM = 1024;
constexpr int NH = 32;

__device__ __align__(1024) __nv_bfloat16 g_qkv[2 * 3 * NH * SEQ * 32];
__device__ __align__(1024) __nv_bfloat16 g_o[2 * SEQ * DM];
__device__ float g_norm[3 * NH * 128];
__device__ __align__(16) float g_kvp[NH * 8 * 64 * 40];

#define TS(k, e) do {} while (0)
#define TSC(k, e) do {} while (0)

struct TMaps {
    CUtensorMap x[2];
    CUtensorMap w[2];
    CUtensorMap phi;
    CUtensorMap qkv64;
    CUtensorMap qkv128;
    CUtensorMap o;
    CUtensorMap wo[2];
    CUtensorMap out;
};

__device__ __forceinline__ uint32_t smem_u32(const void* p) { return (uint32_t)__cvta_generic_to_shared(p); }
__device__ __forceinline__ void mbar_init(uint32_t bar, uint32_t cnt) {
    asm volatile("mbarrier.init.shared::cta.b64 [%0], %1;" ::"r"(bar), "r"(cnt) : "memory");
}
__device__ __forceinline__ void mbar_expect_tx(uint32_t bar, uint32_t bytes) {
    asm volatile("mbarrier.arrive.expect_tx.shared::cta.b64 _, [%0], %1;" ::"r"(bar), "r"(bytes) : "memory");
}
__device__ __forceinline__ void mbar_arrive(uint32_t bar) {
    asm volatile("mbarrier.arrive.shared::cta.b64 _, [%0];" ::"r"(bar) : "memory");
}
__device__ __forceinline__ void mbar_wait(uint32_t bar, uint32_t parity) {
    asm volatile(
        "{\n"
        ".reg .pred p;\n"
        ".reg .u32 n;\n"
        "mbarrier.try_wait.parity.shared::cta.b64 p, [%0], %1;\n"
        "@p bra DONE;\n"
        "mov.u32 n, 0;\n"
        "LAB_WAIT:\n"
        "mbarrier.try_wait.parity.shared::cta.b64 p, [%0], %1;\n"
        "@p bra DONE;\n"
        "add.u32 n, n, 1;\n"
        "setp.lt.u32 p, n, 4194304;\n"
        "@p bra LAB_WAIT;\n"
        "trap;\n"
        "DONE:\n"
        "}\n" ::"r"(bar), "r"(parity) : "memory");
}
__device__ __forceinline__ void tma_load(uint32_t dst, const CUtensorMap* m, uint32_t bar, int c0, int c1) {
    asm volatile("cp.async.bulk.tensor.2d.shared::cluster.global.mbarrier::complete_tx::bytes [%0], [%1, {%3, %4}], [%2];"
                 ::"r"(dst), "l"(m), "r"(bar), "r"(c0), "r"(c1) : "memory");
}
__device__ __forceinline__ void tma_store(const CUtensorMap* m, uint32_t src, int c0, int c1) {
    asm volatile("cp.async.bulk.tensor.2d.global.shared::cta.bulk_group [%0, {%2, %3}], [%1];"
                 ::"l"(m), "r"(src), "r"(c0), "r"(c1) : "memory");
}
__device__ __forceinline__ void bulk_commit() { asm volatile("cp.async.bulk.commit_group;" ::: "memory"); }
template <int N> __device__ __forceinline__ void bulk_wait_read() { asm volatile("cp.async.bulk.wait_group.read %0;" ::"n"(N) : "memory"); }
template <int N> __device__ __forceinline__ void bulk_wait() { asm volatile("cp.async.bulk.wait_group %0;" ::"n"(N) : "memory"); }
__device__ __forceinline__ void prefetch_tmap(const CUtensorMap* m) { asm volatile("prefetch.tensormap [%0];" ::"l"(m) : "memory"); }
__device__ __forceinline__ void fence_async_smem() { asm volatile("fence.proxy.async.shared::cta;" ::: "memory"); }
__device__ __forceinline__ void fence_mbar_init() { asm volatile("fence.mbarrier_init.release.cluster;" ::: "memory"); }
__device__ __forceinline__ void bar_sync(int id, int n) { asm volatile("bar.sync %0, %1;" ::"r"(id), "r"(n) : "memory"); }
__device__ __forceinline__ void bar_arrive(int id, int n) { asm volatile("bar.arrive %0, %1;" ::"r"(id), "r"(n) : "memory"); }
__device__ __forceinline__ void pdl_wait() { asm volatile("griddepcontrol.wait;" ::: "memory"); }
__device__ __forceinline__ void pdl_launch() { asm volatile("griddepcontrol.launch_dependents;" ::: "memory"); }
template <int R> __device__ __forceinline__ void reg_inc() { asm volatile("setmaxnreg.inc.sync.aligned.u32 %0;" ::"n"(R)); }
template <int R> __device__ __forceinline__ void reg_dec() { asm volatile("setmaxnreg.dec.sync.aligned.u32 %0;" ::"n"(R)); }

__device__ __forceinline__ void wg_fence() { asm volatile("wgmma.fence.sync.aligned;" ::: "memory"); }
__device__ __forceinline__ void wg_commit() { asm volatile("wgmma.commit_group.sync.aligned;" ::: "memory"); }
template <int N> __device__ __forceinline__ void wg_wait() { asm volatile("wgmma.wait_group.sync.aligned %0;" ::"n"(N) : "memory"); }
template <int N> __device__ __forceinline__ void fence_regs(float* d) {
#pragma unroll
    for (int i = 0; i < N; i++) asm volatile("" : "+f"(d[i])::"memory");
}
template <int N> __device__ __forceinline__ void fence_regs_u(uint32_t* d) {
#pragma unroll
    for (int i = 0; i < N; i++) asm volatile("" : "+r"(d[i])::"memory");
}
__device__ __forceinline__ uint32_t desc_lo(uint32_t addr, uint32_t lbo) { return ((addr & 0x3FFFF) >> 4) | ((lbo >> 4) << 16); }
__device__ __forceinline__ bool elect_one() {
    uint32_t p;
    asm volatile("{\n.reg .pred p;\nelect.sync _|p, 0xffffffff;\nselp.u32 %0, 1, 0, p;\n}" : "=r"(p));
    return p != 0;
}
__device__ __forceinline__ void mbar_arrive_lane0(uint32_t bar) {
    asm volatile("{\n.reg .pred p;\n.reg .u32 l;\nmov.u32 l, %%laneid;\nsetp.eq.u32 p, l, 0;\n@p mbarrier.arrive.shared::cta.b64 _, [%0];\n}" ::"r"(bar) : "memory");
}
__device__ __forceinline__ uint32_t pack_bf16(float lo, float hi) {
    uint32_t r;
    asm("cvt.rn.bf16x2.f32 %0, %1, %2;" : "=r"(r) : "f"(hi), "f"(lo));
    return r;
}
__device__ __forceinline__ void stsm_x4(uint32_t addr, uint32_t r0, uint32_t r1, uint32_t r2, uint32_t r3) {
    asm volatile("stmatrix.sync.aligned.m8n8.x4.shared.b16 [%0], {%1, %2, %3, %4};" ::"r"(addr), "r"(r0), "r"(r1), "r"(r2), "r"(r3) : "memory");
}
__device__ __forceinline__ void ldsm_x4(uint32_t addr, uint32_t& r0, uint32_t& r1, uint32_t& r2, uint32_t& r3) {
    asm volatile("ldmatrix.sync.aligned.m8n8.x4.shared.b16 {%0, %1, %2, %3}, [%4];" : "=r"(r0), "=r"(r1), "=r"(r2), "=r"(r3) : "r"(addr) : "memory");
}
__device__ __forceinline__ float nanmax(float a, float b) {
    float r;
    asm("max.NaN.f32 %0, %1, %2;" : "=f"(r) : "f"(a), "f"(b));
    return r;
}
__device__ __forceinline__ float ex2(float x) {
    float y;
    asm("ex2.approx.ftz.f32 %0, %1;" : "=f"(y) : "f"(x));
    return y;
}
__device__ __forceinline__ float ex2_poly(float x) {
    float t = x + 12582912.f;
    float r = t - 12582912.f;
    float f = x - r;
    float p = fmaf(0.055171772837638855f, f, 0.2426113784313202f);
    p = fmaf(p, f, 0.6932609677314758f);
    p = fmaf(p, f, 0.9999279975891113f);
    return __int_as_float(__float_as_int(p) + (__float_as_int(t) << 23));
}

struct TrueT { static constexpr bool value = true; };
struct FalseT { static constexpr bool value = false; };

__device__ __forceinline__ void wg_ss128_z(float* d, uint32_t da, uint32_t db) {
    asm volatile("{\n.reg .b64 da, db;\nmov.b64 da, {%64, 0x40000040};\nmov.b64 db, {%65, 0x40000040};\n"
        "wgmma.mma_async.sync.aligned.m64n128k16.f32.bf16.bf16 {%0, %1, %2, %3, %4, %5, %6, %7, %8, %9, %10, %11, %12, %13, %14, %15, %16, %17, %18, %19, %20, %21, %22, %23, %24, %25, %26, %27, %28, %29, %30, %31, %32, %33, %34, %35, %36, %37, %38, %39, %40, %41, %42, %43, %44, %45, %46, %47, %48, %49, %50, %51, %52, %53, %54, %55, %56, %57, %58, %59, %60, %61, %62, %63}, da, db, 0, 1, 1, 0, 1;\n}"
        : "=f"(d[0]), "=f"(d[1]), "=f"(d[2]), "=f"(d[3]), "=f"(d[4]), "=f"(d[5]), "=f"(d[6]), "=f"(d[7]), "=f"(d[8]), "=f"(d[9]), "=f"(d[10]), "=f"(d[11]), "=f"(d[12]), "=f"(d[13]), "=f"(d[14]), "=f"(d[15]), "=f"(d[16]), "=f"(d[17]), "=f"(d[18]), "=f"(d[19]), "=f"(d[20]), "=f"(d[21]), "=f"(d[22]), "=f"(d[23]), "=f"(d[24]), "=f"(d[25]), "=f"(d[26]), "=f"(d[27]), "=f"(d[28]), "=f"(d[29]), "=f"(d[30]), "=f"(d[31]), "=f"(d[32]), "=f"(d[33]), "=f"(d[34]), "=f"(d[35]), "=f"(d[36]), "=f"(d[37]), "=f"(d[38]), "=f"(d[39]), "=f"(d[40]), "=f"(d[41]), "=f"(d[42]), "=f"(d[43]), "=f"(d[44]), "=f"(d[45]), "=f"(d[46]), "=f"(d[47]), "=f"(d[48]), "=f"(d[49]), "=f"(d[50]), "=f"(d[51]), "=f"(d[52]), "=f"(d[53]), "=f"(d[54]), "=f"(d[55]), "=f"(d[56]), "=f"(d[57]), "=f"(d[58]), "=f"(d[59]), "=f"(d[60]), "=f"(d[61]), "=f"(d[62]), "=f"(d[63]) : "r"(da), "r"(db));
}
__device__ __forceinline__ void wg_ss128(float* d, uint32_t da, uint32_t db) {
    asm volatile("{\n.reg .b64 da, db;\nmov.b64 da, {%64, 0x40000040};\nmov.b64 db, {%65, 0x40000040};\n"
        "wgmma.mma_async.sync.aligned.m64n128k16.f32.bf16.bf16 {%0, %1, %2, %3, %4, %5, %6, %7, %8, %9, %10, %11, %12, %13, %14, %15, %16, %17, %18, %19, %20, %21, %22, %23, %24, %25, %26, %27, %28, %29, %30, %31, %32, %33, %34, %35, %36, %37, %38, %39, %40, %41, %42, %43, %44, %45, %46, %47, %48, %49, %50, %51, %52, %53, %54, %55, %56, %57, %58, %59, %60, %61, %62, %63}, da, db, 1, 1, 1, 0, 1;\n}"
        : "+f"(d[0]), "+f"(d[1]), "+f"(d[2]), "+f"(d[3]), "+f"(d[4]), "+f"(d[5]), "+f"(d[6]), "+f"(d[7]), "+f"(d[8]), "+f"(d[9]), "+f"(d[10]), "+f"(d[11]), "+f"(d[12]), "+f"(d[13]), "+f"(d[14]), "+f"(d[15]), "+f"(d[16]), "+f"(d[17]), "+f"(d[18]), "+f"(d[19]), "+f"(d[20]), "+f"(d[21]), "+f"(d[22]), "+f"(d[23]), "+f"(d[24]), "+f"(d[25]), "+f"(d[26]), "+f"(d[27]), "+f"(d[28]), "+f"(d[29]), "+f"(d[30]), "+f"(d[31]), "+f"(d[32]), "+f"(d[33]), "+f"(d[34]), "+f"(d[35]), "+f"(d[36]), "+f"(d[37]), "+f"(d[38]), "+f"(d[39]), "+f"(d[40]), "+f"(d[41]), "+f"(d[42]), "+f"(d[43]), "+f"(d[44]), "+f"(d[45]), "+f"(d[46]), "+f"(d[47]), "+f"(d[48]), "+f"(d[49]), "+f"(d[50]), "+f"(d[51]), "+f"(d[52]), "+f"(d[53]), "+f"(d[54]), "+f"(d[55]), "+f"(d[56]), "+f"(d[57]), "+f"(d[58]), "+f"(d[59]), "+f"(d[60]), "+f"(d[61]), "+f"(d[62]), "+f"(d[63]) : "r"(da), "r"(db));
}
__device__ __forceinline__ void wg_ss192_z(float* d, uint32_t da, uint32_t db) {
    asm volatile("{\n.reg .b64 da, db;\nmov.b64 da, {%96, 0x40000040};\nmov.b64 db, {%97, 0x40000040};\n"
        "wgmma.mma_async.sync.aligned.m64n192k16.f32.bf16.bf16 {%0, %1, %2, %3, %4, %5, %6, %7, %8, %9, %10, %11, %12, %13, %14, %15, %16, %17, %18, %19, %20, %21, %22, %23, %24, %25, %26, %27, %28, %29, %30, %31, %32, %33, %34, %35, %36, %37, %38, %39, %40, %41, %42, %43, %44, %45, %46, %47, %48, %49, %50, %51, %52, %53, %54, %55, %56, %57, %58, %59, %60, %61, %62, %63, %64, %65, %66, %67, %68, %69, %70, %71, %72, %73, %74, %75, %76, %77, %78, %79, %80, %81, %82, %83, %84, %85, %86, %87, %88, %89, %90, %91, %92, %93, %94, %95}, da, db, 0, 1, 1, 0, 1;\n}"
        : "=f"(d[0]), "=f"(d[1]), "=f"(d[2]), "=f"(d[3]), "=f"(d[4]), "=f"(d[5]), "=f"(d[6]), "=f"(d[7]), "=f"(d[8]), "=f"(d[9]), "=f"(d[10]), "=f"(d[11]), "=f"(d[12]), "=f"(d[13]), "=f"(d[14]), "=f"(d[15]), "=f"(d[16]), "=f"(d[17]), "=f"(d[18]), "=f"(d[19]), "=f"(d[20]), "=f"(d[21]), "=f"(d[22]), "=f"(d[23]), "=f"(d[24]), "=f"(d[25]), "=f"(d[26]), "=f"(d[27]), "=f"(d[28]), "=f"(d[29]), "=f"(d[30]), "=f"(d[31]), "=f"(d[32]), "=f"(d[33]), "=f"(d[34]), "=f"(d[35]), "=f"(d[36]), "=f"(d[37]), "=f"(d[38]), "=f"(d[39]), "=f"(d[40]), "=f"(d[41]), "=f"(d[42]), "=f"(d[43]), "=f"(d[44]), "=f"(d[45]), "=f"(d[46]), "=f"(d[47]), "=f"(d[48]), "=f"(d[49]), "=f"(d[50]), "=f"(d[51]), "=f"(d[52]), "=f"(d[53]), "=f"(d[54]), "=f"(d[55]), "=f"(d[56]), "=f"(d[57]), "=f"(d[58]), "=f"(d[59]), "=f"(d[60]), "=f"(d[61]), "=f"(d[62]), "=f"(d[63]), "=f"(d[64]), "=f"(d[65]), "=f"(d[66]), "=f"(d[67]), "=f"(d[68]), "=f"(d[69]), "=f"(d[70]), "=f"(d[71]), "=f"(d[72]), "=f"(d[73]), "=f"(d[74]), "=f"(d[75]), "=f"(d[76]), "=f"(d[77]), "=f"(d[78]), "=f"(d[79]), "=f"(d[80]), "=f"(d[81]), "=f"(d[82]), "=f"(d[83]), "=f"(d[84]), "=f"(d[85]), "=f"(d[86]), "=f"(d[87]), "=f"(d[88]), "=f"(d[89]), "=f"(d[90]), "=f"(d[91]), "=f"(d[92]), "=f"(d[93]), "=f"(d[94]), "=f"(d[95]) : "r"(da), "r"(db));
}
__device__ __forceinline__ void wg_ss192(float* d, uint32_t da, uint32_t db) {
    asm volatile("{\n.reg .b64 da, db;\nmov.b64 da, {%96, 0x40000040};\nmov.b64 db, {%97, 0x40000040};\n"
        "wgmma.mma_async.sync.aligned.m64n192k16.f32.bf16.bf16 {%0, %1, %2, %3, %4, %5, %6, %7, %8, %9, %10, %11, %12, %13, %14, %15, %16, %17, %18, %19, %20, %21, %22, %23, %24, %25, %26, %27, %28, %29, %30, %31, %32, %33, %34, %35, %36, %37, %38, %39, %40, %41, %42, %43, %44, %45, %46, %47, %48, %49, %50, %51, %52, %53, %54, %55, %56, %57, %58, %59, %60, %61, %62, %63, %64, %65, %66, %67, %68, %69, %70, %71, %72, %73, %74, %75, %76, %77, %78, %79, %80, %81, %82, %83, %84, %85, %86, %87, %88, %89, %90, %91, %92, %93, %94, %95}, da, db, 1, 1, 1, 0, 1;\n}"
        : "+f"(d[0]), "+f"(d[1]), "+f"(d[2]), "+f"(d[3]), "+f"(d[4]), "+f"(d[5]), "+f"(d[6]), "+f"(d[7]), "+f"(d[8]), "+f"(d[9]), "+f"(d[10]), "+f"(d[11]), "+f"(d[12]), "+f"(d[13]), "+f"(d[14]), "+f"(d[15]), "+f"(d[16]), "+f"(d[17]), "+f"(d[18]), "+f"(d[19]), "+f"(d[20]), "+f"(d[21]), "+f"(d[22]), "+f"(d[23]), "+f"(d[24]), "+f"(d[25]), "+f"(d[26]), "+f"(d[27]), "+f"(d[28]), "+f"(d[29]), "+f"(d[30]), "+f"(d[31]), "+f"(d[32]), "+f"(d[33]), "+f"(d[34]), "+f"(d[35]), "+f"(d[36]), "+f"(d[37]), "+f"(d[38]), "+f"(d[39]), "+f"(d[40]), "+f"(d[41]), "+f"(d[42]), "+f"(d[43]), "+f"(d[44]), "+f"(d[45]), "+f"(d[46]), "+f"(d[47]), "+f"(d[48]), "+f"(d[49]), "+f"(d[50]), "+f"(d[51]), "+f"(d[52]), "+f"(d[53]), "+f"(d[54]), "+f"(d[55]), "+f"(d[56]), "+f"(d[57]), "+f"(d[58]), "+f"(d[59]), "+f"(d[60]), "+f"(d[61]), "+f"(d[62]), "+f"(d[63]), "+f"(d[64]), "+f"(d[65]), "+f"(d[66]), "+f"(d[67]), "+f"(d[68]), "+f"(d[69]), "+f"(d[70]), "+f"(d[71]), "+f"(d[72]), "+f"(d[73]), "+f"(d[74]), "+f"(d[75]), "+f"(d[76]), "+f"(d[77]), "+f"(d[78]), "+f"(d[79]), "+f"(d[80]), "+f"(d[81]), "+f"(d[82]), "+f"(d[83]), "+f"(d[84]), "+f"(d[85]), "+f"(d[86]), "+f"(d[87]), "+f"(d[88]), "+f"(d[89]), "+f"(d[90]), "+f"(d[91]), "+f"(d[92]), "+f"(d[93]), "+f"(d[94]), "+f"(d[95]) : "r"(da), "r"(db));
}
__device__ __forceinline__ void wg_ss256_z(float* d, uint32_t da, uint32_t db) {
    asm volatile("{\n.reg .b64 da, db;\nmov.b64 da, {%128, 0x40000040};\nmov.b64 db, {%129, 0x40000040};\n"
        "wgmma.mma_async.sync.aligned.m64n256k16.f32.bf16.bf16 {%0, %1, %2, %3, %4, %5, %6, %7, %8, %9, %10, %11, %12, %13, %14, %15, %16, %17, %18, %19, %20, %21, %22, %23, %24, %25, %26, %27, %28, %29, %30, %31, %32, %33, %34, %35, %36, %37, %38, %39, %40, %41, %42, %43, %44, %45, %46, %47, %48, %49, %50, %51, %52, %53, %54, %55, %56, %57, %58, %59, %60, %61, %62, %63, %64, %65, %66, %67, %68, %69, %70, %71, %72, %73, %74, %75, %76, %77, %78, %79, %80, %81, %82, %83, %84, %85, %86, %87, %88, %89, %90, %91, %92, %93, %94, %95, %96, %97, %98, %99, %100, %101, %102, %103, %104, %105, %106, %107, %108, %109, %110, %111, %112, %113, %114, %115, %116, %117, %118, %119, %120, %121, %122, %123, %124, %125, %126, %127}, da, db, 0, 1, 1, 0, 1;\n}"
        : "=f"(d[0]), "=f"(d[1]), "=f"(d[2]), "=f"(d[3]), "=f"(d[4]), "=f"(d[5]), "=f"(d[6]), "=f"(d[7]), "=f"(d[8]), "=f"(d[9]), "=f"(d[10]), "=f"(d[11]), "=f"(d[12]), "=f"(d[13]), "=f"(d[14]), "=f"(d[15]), "=f"(d[16]), "=f"(d[17]), "=f"(d[18]), "=f"(d[19]), "=f"(d[20]), "=f"(d[21]), "=f"(d[22]), "=f"(d[23]), "=f"(d[24]), "=f"(d[25]), "=f"(d[26]), "=f"(d[27]), "=f"(d[28]), "=f"(d[29]), "=f"(d[30]), "=f"(d[31]), "=f"(d[32]), "=f"(d[33]), "=f"(d[34]), "=f"(d[35]), "=f"(d[36]), "=f"(d[37]), "=f"(d[38]), "=f"(d[39]), "=f"(d[40]), "=f"(d[41]), "=f"(d[42]), "=f"(d[43]), "=f"(d[44]), "=f"(d[45]), "=f"(d[46]), "=f"(d[47]), "=f"(d[48]), "=f"(d[49]), "=f"(d[50]), "=f"(d[51]), "=f"(d[52]), "=f"(d[53]), "=f"(d[54]), "=f"(d[55]), "=f"(d[56]), "=f"(d[57]), "=f"(d[58]), "=f"(d[59]), "=f"(d[60]), "=f"(d[61]), "=f"(d[62]), "=f"(d[63]), "=f"(d[64]), "=f"(d[65]), "=f"(d[66]), "=f"(d[67]), "=f"(d[68]), "=f"(d[69]), "=f"(d[70]), "=f"(d[71]), "=f"(d[72]), "=f"(d[73]), "=f"(d[74]), "=f"(d[75]), "=f"(d[76]), "=f"(d[77]), "=f"(d[78]), "=f"(d[79]), "=f"(d[80]), "=f"(d[81]), "=f"(d[82]), "=f"(d[83]), "=f"(d[84]), "=f"(d[85]), "=f"(d[86]), "=f"(d[87]), "=f"(d[88]), "=f"(d[89]), "=f"(d[90]), "=f"(d[91]), "=f"(d[92]), "=f"(d[93]), "=f"(d[94]), "=f"(d[95]), "=f"(d[96]), "=f"(d[97]), "=f"(d[98]), "=f"(d[99]), "=f"(d[100]), "=f"(d[101]), "=f"(d[102]), "=f"(d[103]), "=f"(d[104]), "=f"(d[105]), "=f"(d[106]), "=f"(d[107]), "=f"(d[108]), "=f"(d[109]), "=f"(d[110]), "=f"(d[111]), "=f"(d[112]), "=f"(d[113]), "=f"(d[114]), "=f"(d[115]), "=f"(d[116]), "=f"(d[117]), "=f"(d[118]), "=f"(d[119]), "=f"(d[120]), "=f"(d[121]), "=f"(d[122]), "=f"(d[123]), "=f"(d[124]), "=f"(d[125]), "=f"(d[126]), "=f"(d[127]) : "r"(da), "r"(db));
}
__device__ __forceinline__ void wg_ss256(float* d, uint32_t da, uint32_t db) {
    asm volatile("{\n.reg .b64 da, db;\nmov.b64 da, {%128, 0x40000040};\nmov.b64 db, {%129, 0x40000040};\n"
        "wgmma.mma_async.sync.aligned.m64n256k16.f32.bf16.bf16 {%0, %1, %2, %3, %4, %5, %6, %7, %8, %9, %10, %11, %12, %13, %14, %15, %16, %17, %18, %19, %20, %21, %22, %23, %24, %25, %26, %27, %28, %29, %30, %31, %32, %33, %34, %35, %36, %37, %38, %39, %40, %41, %42, %43, %44, %45, %46, %47, %48, %49, %50, %51, %52, %53, %54, %55, %56, %57, %58, %59, %60, %61, %62, %63, %64, %65, %66, %67, %68, %69, %70, %71, %72, %73, %74, %75, %76, %77, %78, %79, %80, %81, %82, %83, %84, %85, %86, %87, %88, %89, %90, %91, %92, %93, %94, %95, %96, %97, %98, %99, %100, %101, %102, %103, %104, %105, %106, %107, %108, %109, %110, %111, %112, %113, %114, %115, %116, %117, %118, %119, %120, %121, %122, %123, %124, %125, %126, %127}, da, db, 1, 1, 1, 0, 1;\n}"
        : "+f"(d[0]), "+f"(d[1]), "+f"(d[2]), "+f"(d[3]), "+f"(d[4]), "+f"(d[5]), "+f"(d[6]), "+f"(d[7]), "+f"(d[8]), "+f"(d[9]), "+f"(d[10]), "+f"(d[11]), "+f"(d[12]), "+f"(d[13]), "+f"(d[14]), "+f"(d[15]), "+f"(d[16]), "+f"(d[17]), "+f"(d[18]), "+f"(d[19]), "+f"(d[20]), "+f"(d[21]), "+f"(d[22]), "+f"(d[23]), "+f"(d[24]), "+f"(d[25]), "+f"(d[26]), "+f"(d[27]), "+f"(d[28]), "+f"(d[29]), "+f"(d[30]), "+f"(d[31]), "+f"(d[32]), "+f"(d[33]), "+f"(d[34]), "+f"(d[35]), "+f"(d[36]), "+f"(d[37]), "+f"(d[38]), "+f"(d[39]), "+f"(d[40]), "+f"(d[41]), "+f"(d[42]), "+f"(d[43]), "+f"(d[44]), "+f"(d[45]), "+f"(d[46]), "+f"(d[47]), "+f"(d[48]), "+f"(d[49]), "+f"(d[50]), "+f"(d[51]), "+f"(d[52]), "+f"(d[53]), "+f"(d[54]), "+f"(d[55]), "+f"(d[56]), "+f"(d[57]), "+f"(d[58]), "+f"(d[59]), "+f"(d[60]), "+f"(d[61]), "+f"(d[62]), "+f"(d[63]), "+f"(d[64]), "+f"(d[65]), "+f"(d[66]), "+f"(d[67]), "+f"(d[68]), "+f"(d[69]), "+f"(d[70]), "+f"(d[71]), "+f"(d[72]), "+f"(d[73]), "+f"(d[74]), "+f"(d[75]), "+f"(d[76]), "+f"(d[77]), "+f"(d[78]), "+f"(d[79]), "+f"(d[80]), "+f"(d[81]), "+f"(d[82]), "+f"(d[83]), "+f"(d[84]), "+f"(d[85]), "+f"(d[86]), "+f"(d[87]), "+f"(d[88]), "+f"(d[89]), "+f"(d[90]), "+f"(d[91]), "+f"(d[92]), "+f"(d[93]), "+f"(d[94]), "+f"(d[95]), "+f"(d[96]), "+f"(d[97]), "+f"(d[98]), "+f"(d[99]), "+f"(d[100]), "+f"(d[101]), "+f"(d[102]), "+f"(d[103]), "+f"(d[104]), "+f"(d[105]), "+f"(d[106]), "+f"(d[107]), "+f"(d[108]), "+f"(d[109]), "+f"(d[110]), "+f"(d[111]), "+f"(d[112]), "+f"(d[113]), "+f"(d[114]), "+f"(d[115]), "+f"(d[116]), "+f"(d[117]), "+f"(d[118]), "+f"(d[119]), "+f"(d[120]), "+f"(d[121]), "+f"(d[122]), "+f"(d[123]), "+f"(d[124]), "+f"(d[125]), "+f"(d[126]), "+f"(d[127]) : "r"(da), "r"(db));
}
__device__ __forceinline__ void wg_rs64_z(float* d, uint32_t a0, uint32_t a1, uint32_t a2, uint32_t a3, uint32_t db) {
    asm volatile("{\n.reg .b64 db;\nmov.b64 db, {%36, 0x80000020};\n"
        "wgmma.mma_async.sync.aligned.m64n64k16.f32.bf16.bf16 {%0, %1, %2, %3, %4, %5, %6, %7, %8, %9, %10, %11, %12, %13, %14, %15, %16, %17, %18, %19, %20, %21, %22, %23, %24, %25, %26, %27, %28, %29, %30, %31}, {%32, %33, %34, %35}, db, 0, 1, 1, 0;\n}"
        : "=f"(d[0]), "=f"(d[1]), "=f"(d[2]), "=f"(d[3]), "=f"(d[4]), "=f"(d[5]), "=f"(d[6]), "=f"(d[7]), "=f"(d[8]), "=f"(d[9]), "=f"(d[10]), "=f"(d[11]), "=f"(d[12]), "=f"(d[13]), "=f"(d[14]), "=f"(d[15]), "=f"(d[16]), "=f"(d[17]), "=f"(d[18]), "=f"(d[19]), "=f"(d[20]), "=f"(d[21]), "=f"(d[22]), "=f"(d[23]), "=f"(d[24]), "=f"(d[25]), "=f"(d[26]), "=f"(d[27]), "=f"(d[28]), "=f"(d[29]), "=f"(d[30]), "=f"(d[31]) : "r"(a0), "r"(a1), "r"(a2), "r"(a3), "r"(db));
}
__device__ __forceinline__ void wg_rs64(float* d, uint32_t a0, uint32_t a1, uint32_t a2, uint32_t a3, uint32_t db) {
    asm volatile("{\n.reg .b64 db;\nmov.b64 db, {%36, 0x80000020};\n"
        "wgmma.mma_async.sync.aligned.m64n64k16.f32.bf16.bf16 {%0, %1, %2, %3, %4, %5, %6, %7, %8, %9, %10, %11, %12, %13, %14, %15, %16, %17, %18, %19, %20, %21, %22, %23, %24, %25, %26, %27, %28, %29, %30, %31}, {%32, %33, %34, %35}, db, 1, 1, 1, 0;\n}"
        : "+f"(d[0]), "+f"(d[1]), "+f"(d[2]), "+f"(d[3]), "+f"(d[4]), "+f"(d[5]), "+f"(d[6]), "+f"(d[7]), "+f"(d[8]), "+f"(d[9]), "+f"(d[10]), "+f"(d[11]), "+f"(d[12]), "+f"(d[13]), "+f"(d[14]), "+f"(d[15]), "+f"(d[16]), "+f"(d[17]), "+f"(d[18]), "+f"(d[19]), "+f"(d[20]), "+f"(d[21]), "+f"(d[22]), "+f"(d[23]), "+f"(d[24]), "+f"(d[25]), "+f"(d[26]), "+f"(d[27]), "+f"(d[28]), "+f"(d[29]), "+f"(d[30]), "+f"(d[31]) : "r"(a0), "r"(a1), "r"(a2), "r"(a3), "r"(db));
}
__device__ __forceinline__ void wg_rs40t(float* d, uint32_t a0, uint32_t a1, uint32_t a2, uint32_t a3, uint32_t db) {
    asm volatile("{\n.reg .b64 db;\nmov.b64 db, {%24, 0x80000020};\n"
        "wgmma.mma_async.sync.aligned.m64n40k16.f32.bf16.bf16 {%0, %1, %2, %3, %4, %5, %6, %7, %8, %9, %10, %11, %12, %13, %14, %15, %16, %17, %18, %19}, {%20, %21, %22, %23}, db, 1, 1, 1, 1;\n}"
        : "+f"(d[0]), "+f"(d[1]), "+f"(d[2]), "+f"(d[3]), "+f"(d[4]), "+f"(d[5]), "+f"(d[6]), "+f"(d[7]), "+f"(d[8]), "+f"(d[9]), "+f"(d[10]), "+f"(d[11]), "+f"(d[12]), "+f"(d[13]), "+f"(d[14]), "+f"(d[15]), "+f"(d[16]), "+f"(d[17]), "+f"(d[18]), "+f"(d[19]) : "r"(a0), "r"(a1), "r"(a2), "r"(a3), "r"(db));
}
__device__ __forceinline__ void wg_rs40t_z(float* d, uint32_t a0, uint32_t a1, uint32_t a2, uint32_t a3, uint32_t db) {
    asm volatile("{\n.reg .b64 db;\nmov.b64 db, {%24, 0x80000020};\n"
        "wgmma.mma_async.sync.aligned.m64n40k16.f32.bf16.bf16 {%0, %1, %2, %3, %4, %5, %6, %7, %8, %9, %10, %11, %12, %13, %14, %15, %16, %17, %18, %19}, {%20, %21, %22, %23}, db, 0, 1, 1, 1;\n}"
        : "=f"(d[0]), "=f"(d[1]), "=f"(d[2]), "=f"(d[3]), "=f"(d[4]), "=f"(d[5]), "=f"(d[6]), "=f"(d[7]), "=f"(d[8]), "=f"(d[9]), "=f"(d[10]), "=f"(d[11]), "=f"(d[12]), "=f"(d[13]), "=f"(d[14]), "=f"(d[15]), "=f"(d[16]), "=f"(d[17]), "=f"(d[18]), "=f"(d[19]) : "r"(a0), "r"(a1), "r"(a2), "r"(a3), "r"(db));
}
__device__ __forceinline__ void wg_rs32t_z(float* d, uint32_t a0, uint32_t a1, uint32_t a2, uint32_t a3, uint32_t db) {
    asm volatile("{\n.reg .b64 db;\nmov.b64 db, {%20, 0x80000020};\n"
        "wgmma.mma_async.sync.aligned.m64n32k16.f32.bf16.bf16 {%0, %1, %2, %3, %4, %5, %6, %7, %8, %9, %10, %11, %12, %13, %14, %15}, {%16, %17, %18, %19}, db, 0, 1, 1, 1;\n}"
        : "=f"(d[0]), "=f"(d[1]), "=f"(d[2]), "=f"(d[3]), "=f"(d[4]), "=f"(d[5]), "=f"(d[6]), "=f"(d[7]), "=f"(d[8]), "=f"(d[9]), "=f"(d[10]), "=f"(d[11]), "=f"(d[12]), "=f"(d[13]), "=f"(d[14]), "=f"(d[15]) : "r"(a0), "r"(a1), "r"(a2), "r"(a3), "r"(db));
}
__device__ __forceinline__ void wg_rs32t(float* d, uint32_t a0, uint32_t a1, uint32_t a2, uint32_t a3, uint32_t db) {
    asm volatile("{\n.reg .b64 db;\nmov.b64 db, {%20, 0x80000020};\n"
        "wgmma.mma_async.sync.aligned.m64n32k16.f32.bf16.bf16 {%0, %1, %2, %3, %4, %5, %6, %7, %8, %9, %10, %11, %12, %13, %14, %15}, {%16, %17, %18, %19}, db, 1, 1, 1, 1;\n}"
        : "+f"(d[0]), "+f"(d[1]), "+f"(d[2]), "+f"(d[3]), "+f"(d[4]), "+f"(d[5]), "+f"(d[6]), "+f"(d[7]), "+f"(d[8]), "+f"(d[9]), "+f"(d[10]), "+f"(d[11]), "+f"(d[12]), "+f"(d[13]), "+f"(d[14]), "+f"(d[15]) : "r"(a0), "r"(a1), "r"(a2), "r"(a3), "r"(db));
}
__device__ __forceinline__ void wg_ss40tt(float* d, uint32_t da, uint32_t db) {
    asm volatile("{\n.reg .b64 da, db;\nmov.b64 da, {%20, 0x40000040};\nmov.b64 db, {%21, 0x80000020};\n"
        "wgmma.mma_async.sync.aligned.m64n40k16.f32.bf16.bf16 {%0, %1, %2, %3, %4, %5, %6, %7, %8, %9, %10, %11, %12, %13, %14, %15, %16, %17, %18, %19}, da, db, 1, 1, 1, 1, 1;\n}"
        : "+f"(d[0]), "+f"(d[1]), "+f"(d[2]), "+f"(d[3]), "+f"(d[4]), "+f"(d[5]), "+f"(d[6]), "+f"(d[7]), "+f"(d[8]), "+f"(d[9]), "+f"(d[10]), "+f"(d[11]), "+f"(d[12]), "+f"(d[13]), "+f"(d[14]), "+f"(d[15]), "+f"(d[16]), "+f"(d[17]), "+f"(d[18]), "+f"(d[19]) : "r"(da), "r"(db));
}

constexpr float QSCALE = 0.17677669529663687f * 1.4426950408889634f;

template <int MB, int STAGES> struct QkvCfg {
    static constexpr int BM = 128 * MB;
    static constexpr int A_BYTES = BM * 128;
    static constexpr int B_BYTES = 3 * 8192;
    static constexpr int STAGE = A_BYTES + B_BYTES;
    static constexpr int OFF_STG = STAGES * STAGE;
    static constexpr int OFF_PHI = OFF_STG + 2 * 24576;
    static constexpr int OFF_BAR = OFF_PHI + 4096;
    static constexpr int SMEM = OFF_BAR + 128 + 1024;
    static constexpr int MT = SEQ / BM;
    static constexpr int TPP = MT * 16;
};

template <int MB, int STAGES, int RC, int RP>
__global__ void __launch_bounds__(384, 1)
qkv_gemm_kernel(const __grid_constant__ TMaps tm, int tile_begin, int tile_end, int first_prob) {
    using C = QkvCfg<MB, STAGES>;
    extern __shared__ uint8_t smem_raw[];
    const uint32_t sb = (smem_u32(smem_raw) + 1023) & ~1023u;
    const uint32_t bar_full = sb + C::OFF_BAR, bar_empty = bar_full + 8 * STAGES;
    const uint32_t bar_phi_full = bar_empty + 8 * STAGES, bar_phi_empty = bar_phi_full + 8;
    const int wg = __shfl_sync(0xffffffffu, threadIdx.x >> 7, 0);
    const int warp = __shfl_sync(0xffffffffu, (threadIdx.x >> 5) & 3, 0), lane = threadIdx.x & 31;

    if (threadIdx.x == 0) {
        for (int s = 0; s < STAGES; s++) { mbar_init(bar_full + 8 * s, 1); mbar_init(bar_empty + 8 * s, 8); }
        mbar_init(bar_phi_full, 1);
        mbar_init(bar_phi_empty, 8);
        fence_mbar_init();
    }
    __syncthreads();
    pdl_launch();
    if (threadIdx.x == 0) { TS(0, 0); TSC(5, 0); }

    if (wg == 2) {
        reg_dec<RP>();
        if (warp == 0 && lane == 0) {
            prefetch_tmap(&tm.x[0]); prefetch_tmap(&tm.x[1]); prefetch_tmap(&tm.w[0]); prefetch_tmap(&tm.w[1]);
            int s = 0; uint32_t ph = 1; uint32_t phi_ph = 1;
            for (int t = tile_begin + blockIdx.x; t < tile_end; t += gridDim.x) {
                const int pi = t / C::TPP, tt = t % C::TPP;
                const int prob = pi == 0 ? first_prob : 1 - first_prob;
                const int mt = tt % C::MT, nt = tt / C::MT;
                const CUtensorMap* mx = &tm.x[prob];
                const CUtensorMap* mw = &tm.w[prob];
                for (int kt = 0; kt < 16; kt++) {
                    mbar_wait(bar_empty + 8 * s, ph);
                    const uint32_t st = sb + s * C::STAGE, fb = bar_full + 8 * s;
                    mbar_expect_tx(fb, C::STAGE);
                    tma_load(st, mx, fb, kt * 64, mt * C::BM);
#pragma unroll
                    for (int p = 0; p < 3; p++) tma_load(st + C::A_BYTES + p * 8192, mw, fb, p * 1024 + nt * 64, kt * 64);
                    if (++s == STAGES) { s = 0; ph ^= 1; }
                    if (kt == 2 && prob == 0) {
                        mbar_wait(bar_phi_empty, phi_ph);
                        mbar_expect_tx(bar_phi_full, 4096);
                        tma_load(sb + C::OFF_PHI, &tm.phi, bar_phi_full, 0, nt * 64);
                        phi_ph ^= 1;
                    }
                }
            }
        }
    } else {
        reg_inc<RC>();
        float acc[MB][96];
        int s = 0; uint32_t ph = 0; uint32_t phi_ph = 0;
        for (int t = tile_begin + blockIdx.x; t < tile_end; t += gridDim.x) {
            const int pi = t / C::TPP, tt = t % C::TPP;
            const int prob = pi == 0 ? first_prob : 1 - first_prob;
            const int mt = tt % C::MT, nt = tt / C::MT;
            int prev = 0;
            auto kstep = [&](auto first) {
                mbar_wait(bar_full + 8 * s, ph);
                const uint32_t st = sb + s * C::STAGE;
                const uint32_t dA = desc_lo(st + wg * (64 * MB * 128), 16);
                const uint32_t dB = desc_lo(st + C::A_BYTES, 8192);
                wg_fence();
#pragma unroll
                for (int kk = 0; kk < 4; kk++) {
#pragma unroll
                    for (int mb = 0; mb < MB; mb++) {
                        if (decltype(first)::value && kk == 0) wg_ss192_z(acc[mb], dA + mb * 512 + kk * 2, dB + kk * 128);
                        else wg_ss192(acc[mb], dA + mb * 512 + kk * 2, dB + kk * 128);
                    }
                }
                wg_commit();
                if (!decltype(first)::value) {
                    wg_wait<1>();
                    mbar_arrive_lane0(bar_empty + 8 * prev);
                }
                prev = s;
                if (++s == STAGES) { s = 0; ph ^= 1; }
            };
            kstep(TrueT{});
            if (threadIdx.x == 0) TS(0, t < (int)gridDim.x ? 1 : 4);
#pragma unroll 1
            for (int kt = 1; kt < 16; kt++) kstep(FalseT{});
            wg_wait<0>();
            if (threadIdx.x == 0) TS(0, t < (int)gridDim.x ? 2 : 5);
            mbar_arrive_lane0(bar_empty + 8 * prev);
#pragma unroll
            for (int mb = 0; mb < MB; mb++) fence_regs<96>(acc[mb]);

            uint32_t tidl;
            asm volatile("mov.u32 %0, %%tid.x;" : "=r"(tidl));
            const int lane = tidl & 31;
            const uint32_t stg = sb + C::OFF_STG + (tidl >> 5) * 6144;
            const int strow = (lane & 7) + ((lane >> 3) & 1) * 8;
            const uint32_t st_base = stg + strow * 64;
            const uint32_t st_x = (strow >> 1) & 3, st_c = lane >> 4;
            const uint32_t ld_base = stg + (lane >> 2) * 64 + (((lane & 3) ^ ((lane >> 3) & 3)) << 4);
            if (prob == 0) { mbar_wait(bar_phi_full, phi_ph); phi_ph ^= 1; }
            float nrm[6];
#pragma unroll
            for (int i = 0; i < 6; i++) nrm[i] = 0.f;
#pragma unroll
            for (int mb = 0; mb < MB; mb++) {
                const int tok0 = mt * C::BM + wg * (64 * MB) + mb * 64 + warp * 16;
                float* a = acc[mb];
                auto stage_block = [&](int sbk, const uint32_t* pk) {
                    stsm_x4(st_base + sbk * 1024 + ((st_c ^ st_x) << 4), pk[0], pk[1], pk[2], pk[3]);
                    stsm_x4(st_base + sbk * 1024 + (((2 + st_c) ^ st_x) << 4), pk[4], pk[5], pk[6], pk[7]);
                };
                if (mb > 0) __syncwarp();
                if (prob == 1) {
#pragma unroll
                    for (int p = 0; p < 3; p++) {
#pragma unroll
                        for (int hh = 0; hh < 2; hh++) {
                            float s0 = 0.f, s1 = 0.f;
                            uint32_t pk[8];
#pragma unroll
                            for (int g = 0; g < 4; g++) {
                                const int j = p * 8 + hh * 4 + g;
                                float v0 = a[4 * j], v1 = a[4 * j + 1], v2 = a[4 * j + 2], v3 = a[4 * j + 3];
                                if (p == 0) { v0 *= QSCALE; v1 *= QSCALE; v2 *= QSCALE; v3 *= QSCALE; }
                                if (p < 2) {
                                    s0 = fmaf(v0, v0, s0); s0 = fmaf(v1, v1, s0);
                                    s1 = fmaf(v2, v2, s1); s1 = fmaf(v3, v3, s1);
                                } else {
                                    s0 = nanmax(s0, nanmax(fabsf(v0), fabsf(v1)));
                                    s1 = nanmax(s1, nanmax(fabsf(v2), fabsf(v3)));
                                }
                                pk[2 * g] = pack_bf16(v0, v1); pk[2 * g + 1] = pack_bf16(v2, v3);
                            }
                            nrm[p * 2 + hh] = nanmax(nrm[p * 2 + hh], nanmax(s0, s1));
                            stage_block(p * 2 + hh, pk);
                        }
                    }
                } else {
#pragma unroll
                    for (int hh = 0; hh < 2; hh++) {
                        uint32_t pk[8];
#pragma unroll
                        for (int g = 0; g < 4; g++) {
                            const int j = 16 + hh * 4 + g;
                            pk[2 * g] = pack_bf16(a[4 * j], a[4 * j + 1]); pk[2 * g + 1] = pack_bf16(a[4 * j + 2], a[4 * j + 3]);
                        }
                        stage_block(4 + hh, pk);
                    }
#pragma unroll
                    for (int p = 0; p < 2; p++) {
                        uint32_t fr[16];
                        float f[2][16];
#pragma unroll
                        for (int j = 0; j < 8; j++) {
                            const int jj = p * 8 + j;
                            fr[2 * j] = pack_bf16(a[4 * jj], a[4 * jj + 1]); fr[2 * j + 1] = pack_bf16(a[4 * jj + 2], a[4 * jj + 3]);
                        }
                        fence_regs_u<16>(fr);
                        wg_fence();
#pragma unroll
                        for (int hh = 0; hh < 2; hh++) {
                            const uint32_t dP = desc_lo(sb + C::OFF_PHI + hh * 2048, 16);
                            wg_rs32t_z(f[hh], fr[8 * hh], fr[8 * hh + 1], fr[8 * hh + 2], fr[8 * hh + 3], dP);
                            wg_rs32t(f[hh], fr[8 * hh + 4], fr[8 * hh + 5], fr[8 * hh + 6], fr[8 * hh + 7], dP + 64);
                        }
                        wg_commit();
                        wg_wait<0>();
                        fence_regs<16>(f[0]); fence_regs<16>(f[1]);
#pragma unroll
                        for (int hh = 0; hh < 2; hh++) {
                            uint32_t pk[8];
#pragma unroll
                            for (int g = 0; g < 4; g++) {
                                pk[2 * g] = pack_bf16(f[hh][4 * g], f[hh][4 * g + 1]); pk[2 * g + 1] = pack_bf16(f[hh][4 * g + 2], f[hh][4 * g + 3]);
                            }
                            stage_block(p * 2 + hh, pk);
                        }
                    }
                    if (mb == MB - 1) mbar_arrive_lane0(bar_phi_empty);
                }
                __syncwarp();
#pragma unroll
                for (int sbk = 0; sbk < 6; sbk++) {
                    const int p = sbk >> 1, hh = sbk & 1;
                    uint4* dst = reinterpret_cast<uint4*>(g_qkv + ((size_t)((prob * 3 + p) * NH + nt * 2 + hh) * SEQ + tok0) * 32) + lane;
#pragma unroll
                    for (int i = 0; i < 2; i++) {
                        uint4 v;
                        asm volatile("ld.shared.v4.b32 {%0, %1, %2, %3}, [%4];" : "=r"(v.x), "=r"(v.y), "=r"(v.z), "=r"(v.w) : "r"(ld_base + sbk * 1024 + i * 512) : "memory");
                        dst[i * 32] = v;
                    }
                }
            }
            if (prob == 1) {
#pragma unroll
                for (int o = 4; o < 32; o <<= 1) {
#pragma unroll
                    for (int i = 0; i < 6; i++) nrm[i] = nanmax(nrm[i], __shfl_xor_sync(0xffffffffu, nrm[i], o));
                }
#pragma unroll
                for (int o = 1; o < 4; o <<= 1) {
#pragma unroll
                    for (int i = 0; i < 6; i++) {
                        const float other = __shfl_xor_sync(0xffffffffu, nrm[i], o);
                        nrm[i] = i < 4 ? nrm[i] + other : nanmax(nrm[i], other);
                    }
                }
                if (lane < 6 * MB) {
                    const int i = lane / MB, sl = lane % MB;
                    float v = nrm[0];
#pragma unroll
                    for (int q = 1; q < 6; q++) v = i == q ? nrm[q] : v;
                    g_norm[((i >> 1) * NH + nt * 2 + (i & 1)) * 128 + (mt * 8 + wg * 4 + warp) * MB + sl] = v;
                }
            }
            if (threadIdx.x == 0) TS(0, t < (int)gridDim.x ? 3 : 6);
        }
        if (threadIdx.x == 0) { TS(0, 7); TSC(5, 1); }
    }
}

template <int BN, int STAGES> struct OutCfg {
    static constexpr int A_BYTES = 128 * 128;
    static constexpr int B_BYTES = (BN / 64) * 8192;
    static constexpr int STAGE = A_BYTES + B_BYTES;
    static constexpr int OFF_BAR = STAGES * STAGE;
    static constexpr int SMEM = OFF_BAR + 128 + 1024;
    static constexpr int NT = DM / BN;
};

template <int BN> __device__ __forceinline__ void wg_ss_z(float* d, uint32_t a, uint32_t b);
template <> __device__ __forceinline__ void wg_ss_z<128>(float* d, uint32_t a, uint32_t b) { wg_ss128_z(d, a, b); }
template <> __device__ __forceinline__ void wg_ss_z<256>(float* d, uint32_t a, uint32_t b) { wg_ss256_z(d, a, b); }
template <int BN> __device__ __forceinline__ void wg_ss(float* d, uint32_t a, uint32_t b);
template <> __device__ __forceinline__ void wg_ss<128>(float* d, uint32_t a, uint32_t b) { wg_ss128(d, a, b); }
template <> __device__ __forceinline__ void wg_ss<256>(float* d, uint32_t a, uint32_t b) { wg_ss256(d, a, b); }

template <int BN, int STAGES, int RC, int RP>
__global__ void __launch_bounds__(384, 1)
out_gemm_kernel(const __grid_constant__ TMaps tm, int prob_begin) {
    using C = OutCfg<BN, STAGES>;
    extern __shared__ uint8_t smem_raw[];
    const uint32_t sb = (smem_u32(smem_raw) + 1023) & ~1023u;
    const uint32_t bar_full = sb + C::OFF_BAR, bar_empty = bar_full + 8 * STAGES;
    const int wg = __shfl_sync(0xffffffffu, threadIdx.x >> 7, 0);
    const int warp = __shfl_sync(0xffffffffu, (threadIdx.x >> 5) & 3, 0), lane = threadIdx.x & 31;
    const int t = blockIdx.x;
    const int prob = prob_begin + t / (16 * C::NT);
    const int mt = (t % (16 * C::NT)) % 16, nt = (t % (16 * C::NT)) / 16;

    if (threadIdx.x == 0) {
        for (int s = 0; s < STAGES; s++) { mbar_init(bar_full + 8 * s, 1); mbar_init(bar_empty + 8 * s, 8); }
        fence_mbar_init();
    }
    __syncthreads();

    if (threadIdx.x == 0) TS(4, 0);
    if (wg == 2) {
        reg_dec<RP>();
        if (warp == 0 && lane == 0) {
            const CUtensorMap* mw = &tm.wo[prob];
            prefetch_tmap(mw); prefetch_tmap(&tm.o); prefetch_tmap(&tm.out);
#pragma unroll
            for (int s = 0; s < STAGES; s++) {
                const uint32_t st = sb + s * C::STAGE, fb = bar_full + 8 * s;
                mbar_expect_tx(fb, C::STAGE);
#pragma unroll
                for (int p = 0; p < BN / 64; p++) tma_load(st + C::A_BYTES + p * 8192, mw, fb, nt * BN + p * 64, s * 64);
            }
            pdl_wait();
            TS(4, 1);
#pragma unroll
            for (int s = 0; s < STAGES; s++) tma_load(sb + s * C::STAGE, &tm.o, bar_full + 8 * s, s * 64, prob * SEQ + mt * 128);
            int s = 0; uint32_t ph = 0;
            for (int kt = STAGES; kt < 16; kt++) {
                mbar_wait(bar_empty + 8 * s, ph);
                const uint32_t st = sb + s * C::STAGE, fb = bar_full + 8 * s;
                mbar_expect_tx(fb, C::STAGE);
                tma_load(st, &tm.o, fb, kt * 64, prob * SEQ + mt * 128);
#pragma unroll
                for (int p = 0; p < BN / 64; p++) tma_load(st + C::A_BYTES + p * 8192, mw, fb, nt * BN + p * 64, kt * 64);
                if (++s == STAGES) { s = 0; ph ^= 1; }
            }
        }
    } else {
        reg_inc<RC>();
        float acc[BN / 2];
        int s = 0; uint32_t ph = 0; int prev = 0;
        auto kstep = [&](auto first) {
            mbar_wait(bar_full + 8 * s, ph);
            const uint32_t st = sb + s * C::STAGE;
            const uint32_t dA = desc_lo(st + wg * (64 * 128), 16);
            const uint32_t dB = desc_lo(st + C::A_BYTES, 8192);
            wg_fence();
#pragma unroll
            for (int kk = 0; kk < 4; kk++) {
                if (decltype(first)::value && kk == 0) wg_ss_z<BN>(acc, dA + kk * 2, dB + kk * 128);
                else wg_ss<BN>(acc, dA + kk * 2, dB + kk * 128);
            }
            wg_commit();
            if (!decltype(first)::value) {
                wg_wait<1>();
                mbar_arrive_lane0(bar_empty + 8 * prev);
            }
            prev = s;
            if (++s == STAGES) { s = 0; ph ^= 1; }
        };
        kstep(TrueT{});
        if (threadIdx.x == 0) TS(4, 2);
#pragma unroll 1
        for (int kt = 1; kt < 16; kt++) kstep(FalseT{});
        wg_wait<0>();
        if (threadIdx.x == 0) TS(4, 3);
        fence_regs<BN / 2>(acc);
        bar_sync(3, 256);
        const uint32_t stg = sb + wg * (BN / 64) * 8192;
        const int strow = warp * 16 + (lane & 7) + ((lane >> 3) & 1) * 8;
        const uint32_t st_base = stg + strow * 128;
        const uint32_t st_x = strow & 7, st_c = lane >> 4;
#pragma unroll
        for (int b = 0; b < BN / 64; b++) {
#pragma unroll
            for (int jj = 0; jj < 4; jj++) {
                const int j = b * 8 + jj * 2;
                stsm_x4(st_base + b * 8192 + (((jj * 2 + st_c) ^ st_x) << 4),
                        pack_bf16(acc[4 * j], acc[4 * j + 1]), pack_bf16(acc[4 * j + 2], acc[4 * j + 3]),
                        pack_bf16(acc[4 * j + 4], acc[4 * j + 5]), pack_bf16(acc[4 * j + 6], acc[4 * j + 7]));
            }
        }
        fence_async_smem();
        bar_sync(1 + wg, 128);
        if (warp == 0 && lane == 0) {
#pragma unroll
            for (int b = 0; b < BN / 64; b++) tma_store(&tm.out, stg + b * 8192, prob * DM + nt * BN + b * 64, mt * 128 + wg * 64);
            bulk_commit();
            bulk_wait<0>();
            if (threadIdx.x == 0) TS(4, 4);
        }
    }
}

template <int MASK8> __device__ __forceinline__ void exp_pack8(const float* s, uint32_t* p) {
#pragma unroll
    for (int i = 0; i < 4; i++) {
        float a = s[2 * i], b = s[2 * i + 1];
        a = ((MASK8 >> (2 * i)) & 1) ? ex2_poly(a) : ex2(a);
        b = ((MASK8 >> (2 * i + 1)) & 1) ? ex2_poly(b) : ex2(b);
        p[i] = pack_bf16(a, b);
    }
}

template <int NWG, int KVST> struct AttCfg {
    static constexpr int THREADS = NWG * 128;
    static constexpr int QROWS = NWG * 64;
    static constexpr int KV_STAGE = 16384;
    static constexpr int OFF_Q = KVST * KV_STAGE;
    static constexpr int OFF_ONES = OFF_Q + 2 * QROWS * 64;
    static constexpr int OFF_BAR = OFF_ONES + 1024;
    static constexpr int SMEM = OFF_BAR + 256 + 1024;
    static constexpr int NTASK = NH * (SEQ / QROWS);
};

constexpr float SAFE_BOUND = 90.0f;

template <int NWG, int KVST, int MASK16, int W1, int MINB>
__global__ void __launch_bounds__(NWG * 128, MINB)
attn_kernel(const __grid_constant__ TMaps tm) {
    using C = AttCfg<NWG, KVST>;
    extern __shared__ uint8_t smem_raw[];
    const uint32_t sb = (smem_u32(smem_raw) + 1023) & ~1023u;
    const uint32_t bar_full = sb + C::OFF_BAR, bar_empty = bar_full + 8 * KVST;
    const uint32_t bar_qfull = bar_empty + 8 * KVST, bar_qempty = bar_qfull + 16;
    const int wg = __shfl_sync(0xffffffffu, threadIdx.x >> 7, 0);
    const int warp = __shfl_sync(0xffffffffu, (threadIdx.x >> 5) & 3, 0), lane = threadIdx.x & 31;

    if (threadIdx.x == 0) {
        for (int s = 0; s < KVST; s++) { mbar_init(bar_full + 8 * s, 1); mbar_init(bar_empty + 8 * s, NWG * 4); }
        for (int s = 0; s < 2; s++) { mbar_init(bar_qfull + 8 * s, 1); mbar_init(bar_qempty + 8 * s, NWG * 4); }
        fence_mbar_init();
        prefetch_tmap(&tm.qkv128);
    }
    if (threadIdx.x < 64) {
        asm volatile("st.shared.v4.b32 [%0], {%1, %2, %2, %2};" ::"r"(sb + C::OFF_ONES + threadIdx.x * 16), "r"(0x00003F80u), "r"(0u) : "memory");
        fence_async_smem();
    }
    __syncthreads();
    pdl_launch();
    pdl_wait();
    if (threadIdx.x == 0) TS(3, 0);

    int pr_s = 0, pr_qs = 0, pr_st = 0, pr_t = blockIdx.x;
    uint32_t pr_ph = 1, pr_qph = 1;
    auto produce = [&]() {
        if (wg == 0 && warp == 0) {
            if (pr_t < C::NTASK) {
                const int h = pr_t / (SEQ / C::QROWS), qt = pr_t % (SEQ / C::QROWS);
                if (elect_one()) {
                    if (pr_st == 0) {
                        mbar_wait(bar_qempty + 8 * pr_qs, pr_qph);
                        mbar_expect_tx(bar_qfull + 8 * pr_qs, C::QROWS * 64);
                        const int rowQ = ((3 + 0) * NH + h) * SEQ + qt * C::QROWS;
#pragma unroll
                        for (int i = 0; i < C::QROWS / 128; i++)
                            tma_load(sb + C::OFF_Q + pr_qs * C::QROWS * 64 + i * 8192, &tm.qkv128, bar_qfull + 8 * pr_qs, 0, rowQ + i * 128);
                    }
                    mbar_wait(bar_empty + 8 * pr_s, pr_ph);
                    const uint32_t dst = sb + pr_s * C::KV_STAGE, fb = bar_full + 8 * pr_s;
                    mbar_expect_tx(fb, C::KV_STAGE);
                    tma_load(dst, &tm.qkv128, fb, 0, ((3 + 1) * NH + h) * SEQ + pr_st * 128);
                    tma_load(dst + 8192, &tm.qkv128, fb, 0, ((3 + 2) * NH + h) * SEQ + pr_st * 128);
                }
                __syncwarp();
                if (pr_st == 0) { if (++pr_qs == 2) { pr_qs = 0; pr_qph ^= 1; } }
                if (++pr_s == KVST) { pr_s = 0; pr_ph ^= 1; }
                if (++pr_st == 16) { pr_st = 0; pr_t += gridDim.x; }
            }
        }
    };
#pragma unroll 1
    for (int i = 0; i < KVST - 1; i++) produce();

    int s = 0, qs = 0;
    uint32_t ph = 0, qph = 0;
    const int qrow = wg * 64 + warp * 16 + (lane & 7) + ((lane >> 3) & 1) * 8;
    constexpr uint32_t DV_STEP = 64u - (64u << 16);
    const uint32_t k_lo0 = desc_lo(sb, 16);
    const uint32_t v_lo0 = desc_lo(sb + 8192, C::OFF_ONES - 8192);
    constexpr uint32_t V_STAGE_STEP = 1024u - (1024u << 16);
    for (int t = blockIdx.x; t < C::NTASK; t += gridDim.x) {
        const int h = t / (SEQ / C::QROWS), qt = t % (SEQ / C::QROWS);
        int fast;
        {
            float qm = 0.f, km = 0.f, vm = 0.f;
            bool ok = true;
#pragma unroll
            for (int i = 0; i < 4; i++) {
                const float a = g_norm[(0 * NH + h) * 128 + lane + 32 * i], b = g_norm[(1 * NH + h) * 128 + lane + 32 * i], c = g_norm[(2 * NH + h) * 128 + lane + 32 * i];
                ok = ok && (a < 1e30f) && (b < 1e30f) && (c <= 1048576.f);
                qm = fmaxf(qm, a); km = fmaxf(km, b); vm = fmaxf(vm, c);
            }
#pragma unroll
            for (int o = 1; o < 32; o <<= 1) {
                qm = fmaxf(qm, __shfl_xor_sync(0xffffffffu, qm, o));
                km = fmaxf(km, __shfl_xor_sync(0xffffffffu, km, o));
                vm = fmaxf(vm, __shfl_xor_sync(0xffffffffu, vm, o));
            }
            fast = __all_sync(0xffffffffu, ok && (qm * km * 1.05f <= SAFE_BOUND * SAFE_BOUND) && (vm >= 0.0009765625f));
            fast = __shfl_sync(0xffffffffu, fast, 0);
        }
        uint32_t q[8];
        mbar_wait(bar_qfull + 8 * qs, qph);
        {
            const uint32_t qa = sb + C::OFF_Q + qs * C::QROWS * 64 + qrow * 64;
            const uint32_t x = (qrow >> 1) & 3, c = lane >> 4;
            ldsm_x4(qa + (((0 + c) ^ x) << 4), q[0], q[1], q[2], q[3]);
            ldsm_x4(qa + (((2 + c) ^ x) << 4), q[4], q[5], q[6], q[7]);
        }
        fence_regs_u<8>(q);
        __syncwarp();
        mbar_arrive_lane0(bar_qempty + 8 * qs);
        if (++qs == 2) { qs = 0; qph ^= 1; }

        float o[20];
#pragma unroll
        for (int i = 0; i < 20; i++) o[i] = 0.f;
        fence_regs<20>(o);

        if (fast) {
            float s0[32], s1[32];
            uint32_t p0[16], p1_[16];
            uint32_t* p1 = W1 ? p1_ : p0;
            auto qk = [&](float* sc, uint32_t dK) {
                wg_fence();
                wg_rs64_z(sc, q[0], q[1], q[2], q[3], dK);
                wg_rs64(sc, q[4], q[5], q[6], q[7], dK + 2);
                wg_commit();
            };
            auto exp_pv = [&](const float* sc, uint32_t* p, uint32_t dV) {
#pragma unroll
                for (int kk = 0; kk < 4; kk++) {
                    if (kk & 1) exp_pack8<(MASK16 >> 8) & 0xFF>(sc + 8 * kk, p + 4 * kk);
                    else exp_pack8<MASK16 & 0xFF>(sc + 8 * kk, p + 4 * kk);
                    wg_fence();
                    wg_rs40t(o, p[4 * kk], p[4 * kk + 1], p[4 * kk + 2], p[4 * kk + 3], dV + kk * DV_STEP);
                }
                wg_commit();
            };
            mbar_wait(bar_full + 8 * s, ph);
            qk(s0, k_lo0 + s * 1024);
            wg_wait<0>();
            fence_regs<32>(s0);
            int sprev = s;
#pragma unroll 1
            for (int st = 0; st < 15; st++) {
                const uint32_t dK = k_lo0 + s * 1024, dV = v_lo0 + s * V_STAGE_STEP;
                qk(s1, dK + 256);
                exp_pv(s0, p0, dV);
                if (W1) wg_wait<1>(); else wg_wait<0>();
                fence_regs<32>(s1);
                if (W1) { if (st > 0) mbar_arrive_lane0(bar_empty + 8 * sprev); }
                sprev = s;
                if (++s == KVST) { s = 0; ph ^= 1; }
                mbar_wait(bar_full + 8 * s, ph);
                qk(s0, k_lo0 + s * 1024);
                exp_pv(s1, p1, dV + 4 * DV_STEP);
                if (W1) wg_wait<1>(); else wg_wait<0>();
                fence_regs<32>(s0);
                if (!W1) mbar_arrive_lane0(bar_empty + 8 * sprev);
                produce();
            }
            {
                const uint32_t dK = k_lo0 + s * 1024, dV = v_lo0 + s * V_STAGE_STEP;
                qk(s1, dK + 256);
                exp_pv(s0, p0, dV);
                if (W1) wg_wait<1>(); else wg_wait<0>();
                fence_regs<32>(s1);
                if (W1) mbar_arrive_lane0(bar_empty + 8 * sprev);
                exp_pv(s1, p1, dV + 4 * DV_STEP);
                wg_wait<0>();
                fence_regs<20>(o);
                mbar_arrive_lane0(bar_empty + 8 * s);
                if (++s == KVST) { s = 0; ph ^= 1; }
                produce();
            }
        } else {
            float sc[32];
            uint32_t p[16];
            float m0 = -INFINITY, m1 = -INFINITY;
#pragma unroll 1
            for (int st = 0; st < 16; st++) {
                mbar_wait(bar_full + 8 * s, ph);
                const uint32_t dK = k_lo0 + s * 1024, dV = v_lo0 + s * V_STAGE_STEP;
#pragma unroll 1
                for (int sub = 0; sub < 2; sub++) {
                    wg_fence();
                    wg_rs64_z(sc, q[0], q[1], q[2], q[3], dK + sub * 256);
                    wg_rs64(sc, q[4], q[5], q[6], q[7], dK + sub * 256 + 2);
                    wg_commit();
                    wg_wait<0>();
                    fence_regs<32>(sc);
                    float x0 = m0, x1 = m1;
#pragma unroll
                    for (int j = 0; j < 8; j++) {
                        x0 = fmaxf(x0, fmaxf(sc[4 * j], sc[4 * j + 1]));
                        x1 = fmaxf(x1, fmaxf(sc[4 * j + 2], sc[4 * j + 3]));
                    }
                    x0 = fmaxf(x0, __shfl_xor_sync(0xffffffffu, x0, 1)); x0 = fmaxf(x0, __shfl_xor_sync(0xffffffffu, x0, 2));
                    x1 = fmaxf(x1, __shfl_xor_sync(0xffffffffu, x1, 1)); x1 = fmaxf(x1, __shfl_xor_sync(0xffffffffu, x1, 2));
                    const float al0 = ex2(m0 - x0), al1 = ex2(m1 - x1);
                    m0 = x0; m1 = x1;
#pragma unroll
                    for (int j = 0; j < 5; j++) { o[4 * j] *= al0; o[4 * j + 1] *= al0; o[4 * j + 2] *= al1; o[4 * j + 3] *= al1; }
#pragma unroll
                    for (int j = 0; j < 8; j++) {
                        p[2 * j] = pack_bf16(ex2(sc[4 * j] - x0), ex2(sc[4 * j + 1] - x0));
                        p[2 * j + 1] = pack_bf16(ex2(sc[4 * j + 2] - x1), ex2(sc[4 * j + 3] - x1));
                    }
                    fence_regs<20>(o); fence_regs_u<16>(p);
                    wg_fence();
#pragma unroll
                    for (int kk = 0; kk < 4; kk++) wg_rs40t(o, p[4 * kk], p[4 * kk + 1], p[4 * kk + 2], p[4 * kk + 3], dV + (sub * 4 + kk) * DV_STEP);
                    wg_commit();
                    wg_wait<0>();
                    fence_regs<20>(o);
                }
                mbar_arrive_lane0(bar_empty + 8 * s);
                produce();
                if (++s == KVST) { s = 0; ph ^= 1; }
            }
        }
        const float l0 = __shfl_sync(0xffffffffu, o[16], lane & ~3), l1 = __shfl_sync(0xffffffffu, o[18], lane & ~3);
        const float i0 = 1.0f / l0, i1 = 1.0f / l1;
        const int tok = qt * C::QROWS + wg * 64 + warp * 16 + (lane >> 2);
        uint32_t* dst = reinterpret_cast<uint32_t*>(g_o + (size_t)(SEQ + tok) * DM + h * 32 + (lane & 3) * 2);
#pragma unroll
        for (int j = 0; j < 4; j++) {
            dst[j * 4] = pack_bf16(o[4 * j] * i0, o[4 * j + 1] * i0);
            dst[j * 4 + 8 * (DM / 2)] = pack_bf16(o[4 * j + 2] * i1, o[4 * j + 3] * i1);
        }
        if (threadIdx.x == 0) TS(3, t < (int)gridDim.x ? 1 : (t < 2 * (int)gridDim.x ? 2 : 3));
    }
}

__device__ __forceinline__ void hedgehog_row(const uint4 raw, uint32_t* pos, uint32_t* neg) {
    float x[8];
    const uint32_t w[4] = {raw.x, raw.y, raw.z, raw.w};
#pragma unroll
    for (int i = 0; i < 4; i++) { x[2 * i] = __uint_as_float(w[i] << 16); x[2 * i + 1] = __uint_as_float(w[i] & 0xffff0000u); }
    float mx = x[0], mn = x[0];
#pragma unroll
    for (int i = 1; i < 8; i++) { mx = fmaxf(mx, x[i]); mn = fminf(mn, x[i]); }
    mx = fmaxf(mx, __shfl_xor_sync(0xffffffffu, mx, 1)); mn = fminf(mn, __shfl_xor_sync(0xffffffffu, mn, 1));
    mx = fmaxf(mx, __shfl_xor_sync(0xffffffffu, mx, 2)); mn = fminf(mn, __shfl_xor_sync(0xffffffffu, mn, 2));
    constexpr float L2E = 1.4426950408889634f;
    const float mxs = -mx * L2E, mns = mn * L2E;
    float ep[8], en[8], sp = 0.f, sn = 0.f;
#pragma unroll
    for (int i = 0; i < 8; i++) {
        ep[i] = ex2(fmaf(x[i], L2E, mxs));
        en[i] = ex2(fmaf(x[i], -L2E, mns));
        sp += ep[i]; sn += en[i];
    }
    sp += __shfl_xor_sync(0xffffffffu, sp, 1); sn += __shfl_xor_sync(0xffffffffu, sn, 1);
    sp += __shfl_xor_sync(0xffffffffu, sp, 2); sn += __shfl_xor_sync(0xffffffffu, sn, 2);
    const float ip = 1.0f / sp, in = 1.0f / sn;
#pragma unroll
    for (int i = 0; i < 4; i++) {
        pos[i] = pack_bf16(ep[2 * i] * ip, ep[2 * i + 1] * ip);
        neg[i] = pack_bf16(en[2 * i] * in, en[2 * i + 1] * in);
    }
}

__global__ void __launch_bounds__(128) lin_kv_kernel() {
    __shared__ __align__(1024) uint8_t sm[8192 + 4096 + 1024];
    const uint32_t sphi = smem_u32(sm), sv = sphi + 8192, sones = sv + 4096;
    const int h = blockIdx.x >> 3, ch = blockIdx.x & 7;
    const int warp = threadIdx.x >> 5, lane = threadIdx.x & 31;
    const int r = lane >> 2, c = lane & 3;
    if (threadIdx.x < 64) asm volatile("st.shared.v4.b32 [%0], {%1, %2, %2, %2};" ::"r"(sones + threadIdx.x * 16), "r"(0x00003F80u), "r"(0u) : "memory");
    pdl_launch();
    pdl_wait();
    if (threadIdx.x == 0) TS(1, 0);
    const __nv_bfloat16* gk = g_qkv + (size_t)((0 * 3 + 1) * NH + h) * SEQ * 32;
    const __nv_bfloat16* gv = g_qkv + (size_t)((0 * 3 + 2) * NH + h) * SEQ * 32;
    float acc[20];
#pragma unroll
    for (int i = 0; i < 20; i++) acc[i] = 0.f;
    fence_regs<20>(acc);
    const uint32_t dA = desc_lo(sphi, 16);
    const uint32_t dB = desc_lo(sv, sones - sv);
    const uint32_t DV_STEP = 64u - (64u << 16);
#pragma unroll 1
    for (int mb = 0; mb < 4; mb++) {
        const int tok0 = ch * 256 + mb * 64;
        const int row0 = warp * 16 + r;
        const uint4 k0 = *reinterpret_cast<const uint4*>(gk + (size_t)(tok0 + row0) * 32 + c * 8);
        const uint4 k1 = *reinterpret_cast<const uint4*>(gk + (size_t)(tok0 + row0 + 8) * 32 + c * 8);
        uint4 vv[2];
#pragma unroll
        for (int i = 0; i < 2; i++) {
            const int idx = threadIdx.x + 128 * i;
            vv[i] = *reinterpret_cast<const uint4*>(gv + (size_t)tok0 * 32 + idx * 8);
        }
        uint32_t pos0[4], neg0[4], pos1[4], neg1[4];
        hedgehog_row(k0, pos0, neg0);
        hedgehog_row(k1, pos1, neg1);
        if (mb > 0) __syncthreads();
        {
            const int ra = row0, rb = row0 + 8;
            asm volatile("st.shared.v4.b32 [%0], {%1, %2, %3, %4};" ::"r"(sphi + ra * 128 + ((c ^ (ra & 7)) << 4)), "r"(pos0[0]), "r"(pos0[1]), "r"(pos0[2]), "r"(pos0[3]) : "memory");
            asm volatile("st.shared.v4.b32 [%0], {%1, %2, %3, %4};" ::"r"(sphi + ra * 128 + (((4 + c) ^ (ra & 7)) << 4)), "r"(neg0[0]), "r"(neg0[1]), "r"(neg0[2]), "r"(neg0[3]) : "memory");
            asm volatile("st.shared.v4.b32 [%0], {%1, %2, %3, %4};" ::"r"(sphi + rb * 128 + ((c ^ (rb & 7)) << 4)), "r"(pos1[0]), "r"(pos1[1]), "r"(pos1[2]), "r"(pos1[3]) : "memory");
            asm volatile("st.shared.v4.b32 [%0], {%1, %2, %3, %4};" ::"r"(sphi + rb * 128 + (((4 + c) ^ (rb & 7)) << 4)), "r"(neg1[0]), "r"(neg1[1]), "r"(neg1[2]), "r"(neg1[3]) : "memory");
#pragma unroll
            for (int i = 0; i < 2; i++) {
                const int idx = threadIdx.x + 128 * i, vr = idx >> 2, vc = idx & 3;
                asm volatile("st.shared.v4.b32 [%0], {%1, %2, %3, %4};" ::"r"(sv + vr * 64 + ((vc ^ ((vr >> 1) & 3)) << 4)), "r"(vv[i].x), "r"(vv[i].y), "r"(vv[i].z), "r"(vv[i].w) : "memory");
            }
        }
        fence_async_smem();
        __syncthreads();
        wg_fence();
#pragma unroll
        for (int kk = 0; kk < 4; kk++) wg_ss40tt(acc, dA + kk * 128, dB + kk * DV_STEP);
        wg_commit();
        wg_wait<0>();
        fence_regs<20>(acc);
    }
    if (threadIdx.x == 0) TS(1, 1);
    float* dst = g_kvp + (size_t)(h * 8 + ch) * 2560 + (warp * 16 + r) * 40 + c * 2;
#pragma unroll
    for (int j = 0; j < 5; j++) {
        *reinterpret_cast<float2*>(dst + j * 8) = make_float2(acc[4 * j], acc[4 * j + 1]);
        *reinterpret_cast<float2*>(dst + 8 * 40 + j * 8) = make_float2(acc[4 * j + 2], acc[4 * j + 3]);
    }
}

__global__ void __launch_bounds__(128) lin_out_kernel() {
    __shared__ __align__(1024) uint8_t sm[8192];
    const uint32_t skv = smem_u32(sm);
    const int h = blockIdx.x >> 3, ch = blockIdx.x & 7;
    const int warp = threadIdx.x >> 5, lane = threadIdx.x & 31;
    const int r = lane >> 2, c = lane & 3;
    pdl_launch();
    pdl_wait();
    if (threadIdx.x == 0) TS(2, 0);
    for (int idx = threadIdx.x; idx < 320; idx += 128) {
        const int f = idx / 5, cg = idx % 5;
        float sum[8];
#pragma unroll
        for (int i = 0; i < 8; i++) sum[i] = 0.f;
#pragma unroll
        for (int pp = 0; pp < 8; pp++) {
            const float4* src = reinterpret_cast<const float4*>(g_kvp + (size_t)(h * 8 + pp) * 2560 + f * 40 + cg * 8);
            const float4 a = src[0], b = src[1];
            sum[0] += a.x; sum[1] += a.y; sum[2] += a.z; sum[3] += a.w; sum[4] += b.x; sum[5] += b.y; sum[6] += b.z; sum[7] += b.w;
        }
        const int half = f >> 5, cc = (f >> 3) & 3, i = f & 7;
        const int kp = half * 32 + 16 * (i >> 2) + 8 * ((i >> 1) & 1) + 2 * cc + (i & 1);
        const uint32_t a = skv + (cg == 4 ? 4096 : 0) + kp * 64 + (((cg & 3) ^ ((kp >> 1) & 3)) << 4);
        asm volatile("st.shared.v4.b32 [%0], {%1, %2, %3, %4};" ::"r"(a), "r"(pack_bf16(sum[0], sum[1])), "r"(pack_bf16(sum[2], sum[3])),
                     "r"(pack_bf16(sum[4], sum[5])), "r"(pack_bf16(sum[6], sum[7])) : "memory");
    }
    fence_async_smem();
    __syncthreads();
    const __nv_bfloat16* gq = g_qkv + (size_t)((0 * 3 + 0) * NH + h) * SEQ * 32;
    const uint32_t dB = desc_lo(skv, 4096);
#pragma unroll 1
    for (int mb = 0; mb < 4; mb++) {
        const int tok = ch * 256 + mb * 64 + warp * 16 + r;
        const uint4 q0 = *reinterpret_cast<const uint4*>(gq + (size_t)tok * 32 + c * 8);
        const uint4 q1 = *reinterpret_cast<const uint4*>(gq + (size_t)(tok + 8) * 32 + c * 8);
        uint32_t pos0[4], neg0[4], pos1[4], neg1[4];
        hedgehog_row(q0, pos0, neg0);
        hedgehog_row(q1, pos1, neg1);
        float acc[20];
        fence_regs_u<4>(pos0); fence_regs_u<4>(pos1); fence_regs_u<4>(neg0); fence_regs_u<4>(neg1);
        wg_fence();
        wg_rs40t_z(acc, pos0[0], pos1[0], pos0[1], pos1[1], dB);
        wg_rs40t(acc, pos0[2], pos1[2], pos0[3], pos1[3], dB + 64);
        wg_rs40t(acc, neg0[0], neg1[0], neg0[1], neg1[1], dB + 128);
        wg_rs40t(acc, neg0[2], neg1[2], neg0[3], neg1[3], dB + 192);
        wg_commit();
        wg_wait<0>();
        fence_regs<20>(acc);
        const float d0 = __shfl_sync(0xffffffffu, acc[16], lane & ~3) + 1e-6f, d1 = __shfl_sync(0xffffffffu, acc[18], lane & ~3) + 1e-6f;
        const float i0 = 1.0f / d0, i1 = 1.0f / d1;
        uint32_t* dst = reinterpret_cast<uint32_t*>(g_o + (size_t)tok * DM + h * 32 + c * 2);
#pragma unroll
        for (int j = 0; j < 4; j++) {
            dst[j * 4] = pack_bf16(acc[4 * j] * i0, acc[4 * j + 1] * i0);
            dst[j * 4 + 8 * (DM / 2)] = pack_bf16(acc[4 * j + 2] * i1, acc[4 * j + 3] * i1);
        }
    }
    if (threadIdx.x == 0) TS(2, 1);
}

typedef CUresult (*EncodeFn)(CUtensorMap*, CUtensorMapDataType, cuuint32_t, void*, const cuuint64_t*, const cuuint64_t*,
                             const cuuint32_t*, const cuuint32_t*, CUtensorMapInterleave, CUtensorMapSwizzle,
                             CUtensorMapL2promotion, CUtensorMapFloatOOBfill);

void make_map(EncodeFn enc, CUtensorMap* m, const void* ptr, uint64_t d0, uint64_t d1, uint32_t b0, uint32_t b1, CUtensorMapSwizzle sw) {
    cuuint64_t dims[2] = {d0, d1};
    cuuint64_t strides[1] = {d0 * 2};
    cuuint32_t box[2] = {b0, b1};
    cuuint32_t es[2] = {1, 1};
    enc(m, CU_TENSOR_MAP_DATA_TYPE_BFLOAT16, 2, const_cast<void*>(ptr), dims, strides, box, es, CU_TENSOR_MAP_INTERLEAVE_NONE, sw,
        CU_TENSOR_MAP_L2_PROMOTION_L2_128B, CU_TENSOR_MAP_FLOAT_OOB_FILL_NONE);
}

template <typename... KArgs, typename... Args>
void launch(void (*k)(KArgs...), int grid, int block, int smem, cudaStream_t st, bool pdl, Args... args) {
    cudaLaunchConfig_t cfg = {};
    cfg.gridDim = dim3(grid); cfg.blockDim = dim3(block); cfg.dynamicSmemBytes = smem; cfg.stream = st;
    cudaLaunchAttribute at[1];
    at[0].id = cudaLaunchAttributeProgrammaticStreamSerialization;
    at[0].val.programmaticStreamSerializationAllowed = 1;
    cfg.attrs = at; cfg.numAttrs = pdl ? 1 : 0;
    cudaLaunchKernelEx(&cfg, k, KArgs(args)...);
}

constexpr int K1_MB = 2, K1_ST = 3;
constexpr int K3_BN = 256, K3_ST = 4;
constexpr int K2_NWG = 4, K2_KVST = 4, K2_MASK = 0x1111, K2_W1 = 0;

}

extern "C" void kernel_launch(void* const* d_in, const int* in_sizes, int n_in, void* d_out, int out_size) {
    (void)in_sizes; (void)n_in; (void)out_size;
    static bool init = false;
    static TMaps tm;
    static int nsm = 132;
    static void* cached[8];
    auto k1 = qkv_gemm_kernel<K1_MB, K1_ST, 240, 24>;
    auto k2 = attn_kernel<K2_NWG, K2_KVST, K2_MASK, K2_W1, 1>;
    auto k3 = out_gemm_kernel<K3_BN, K3_ST, 232, 40>;
    bool same = init;
    for (int i = 0; i < 7 && same; i++) same = cached[i] == d_in[i];
    same = same && cached[7] == d_out;
    if (!same) {
        void* fn = nullptr;
        cudaDriverEntryPointQueryResult qr;
        cudaGetDriverEntryPoint("cuTensorMapEncodeTiled", &fn, cudaEnableDefault, &qr);
        EncodeFn enc = (EncodeFn)fn;
        void *pqkv, *po;
        cudaGetSymbolAddress(&pqkv, g_qkv);
        cudaGetSymbolAddress(&po, g_o);
        make_map(enc, &tm.x[0], d_in[0], 1024, 2048, 64, 128 * K1_MB, CU_TENSOR_MAP_SWIZZLE_128B);
        make_map(enc, &tm.x[1], d_in[4], 1024, 2048, 64, 128 * K1_MB, CU_TENSOR_MAP_SWIZZLE_128B);
        make_map(enc, &tm.w[0], d_in[1], 3072, 1024, 64, 64, CU_TENSOR_MAP_SWIZZLE_128B);
        make_map(enc, &tm.w[1], d_in[5], 3072, 1024, 64, 64, CU_TENSOR_MAP_SWIZZLE_128B);
        make_map(enc, &tm.phi, d_in[2], 32, 1024, 32, 64, CU_TENSOR_MAP_SWIZZLE_64B);
        make_map(enc, &tm.qkv64, pqkv, 32, 2 * 3 * NH * SEQ, 32, 64, CU_TENSOR_MAP_SWIZZLE_64B);
        make_map(enc, &tm.qkv128, pqkv, 32, 2 * 3 * NH * SEQ, 32, 128, CU_TENSOR_MAP_SWIZZLE_64B);
        make_map(enc, &tm.o, po, 1024, 2 * SEQ, 64, 128, CU_TENSOR_MAP_SWIZZLE_128B);
        make_map(enc, &tm.wo[0], d_in[3], 1024, 1024, 64, 64, CU_TENSOR_MAP_SWIZZLE_128B);
        make_map(enc, &tm.wo[1], d_in[6], 1024, 1024, 64, 64, CU_TENSOR_MAP_SWIZZLE_128B);
        make_map(enc, &tm.out, d_out, 2048, 2048, 64, 64, CU_TENSOR_MAP_SWIZZLE_128B);
        cudaFuncSetAttribute(k1, cudaFuncAttributeMaxDynamicSharedMemorySize, QkvCfg<K1_MB, K1_ST>::SMEM);
        cudaFuncSetAttribute(k2, cudaFuncAttributeMaxDynamicSharedMemorySize, AttCfg<K2_NWG, K2_KVST>::SMEM);
        cudaFuncSetAttribute(k3, cudaFuncAttributeMaxDynamicSharedMemorySize, OutCfg<K3_BN, K3_ST>::SMEM);
        int dev = 0;
        cudaGetDevice(&dev);
        cudaDeviceGetAttribute(&nsm, cudaDevAttrMultiProcessorCount, dev);
        for (int i = 0; i < 7; i++) cached[i] = d_in[i];
        cached[7] = d_out;
        init = true;
    }
    cudaStream_t st = cudaStreamPerThread;
    const int ntile = 2 * QkvCfg<K1_MB, K1_ST>::TPP;
    launch(k1, ntile < nsm ? ntile : nsm, 384, QkvCfg<K1_MB, K1_ST>::SMEM, st, false, tm, 0, ntile, 1);
    launch(lin_kv_kernel, 256, 128, 0, st, true);
    launch(lin_out_kernel, 256, 128, 0, st, true);
    const int ntask = AttCfg<K2_NWG, K2_KVST>::NTASK;
    launch(k2, ntask < nsm ? ntask : nsm, AttCfg<K2_NWG, K2_KVST>::THREADS, AttCfg<K2_NWG, K2_KVST>::SMEM, st, true, tm);
    launch(k3, 2 * 16 * OutCfg<K3_BN, K3_ST>::NT, 384, OutCfg<K3_BN, K3_ST>::SMEM, st, true, tm, 0);
}
```

```cpp
#include <cuda_runtime.h>
#include <cuda_bf16.h>
#include <cuda.h>
#include <stdint.h>

namespace {

constexpr int SEQ = 2048;
constexpr int DM = 1024;
constexpr int NH = 32;

__device__ __align__(1024) __nv_bfloat16 g_qkv[2 * 3 * NH * SEQ * 32];
__device__ __align__(1024) __nv_bfloat16 g_o[2 * SEQ * DM];
__device__ float g_norm[3 * NH * 128];
__device__ __align__(16) float g_kvp[NH * 8 * 64 * 40];

#define TS(k, e) do {} while (0)
#define TSC(k, e) do {} while (0)

struct TMaps {
    CUtensorMap x[2];
    CUtensorMap w[2];
    CUtensorMap phi;
    CUtensorMap qkv64;
    CUtensorMap qkv128;
    CUtensorMap o;
    CUtensorMap wo[2];
    CUtensorMap out;
};

__device__ __forceinline__ uint32_t smem_u32(const void* p) { return (uint32_t)__cvta_generic_to_shared(p); }
__device__ __forceinline__ void mbar_init(uint32_t bar, uint32_t cnt) {
    asm volatile("mbarrier.init.shared::cta.b64 [%0], %1;" ::"r"(bar), "r"(cnt) : "memory");
}
__device__ __forceinline__ void mbar_expect_tx(uint32_t bar, uint32_t bytes) {
    asm volatile("mbarrier.arrive.expect_tx.shared::cta.b64 _, [%0], %1;" ::"r"(bar), "r"(bytes) : "memory");
}
__device__ __forceinline__ void mbar_arrive(uint32_t bar) {
    asm volatile("mbarrier.arrive.shared::cta.b64 _, [%0];" ::"r"(bar) : "memory");
}
__device__ __forceinline__ void mbar_wait(uint32_t bar, uint32_t parity) {
    asm volatile(
        "{\n"
        ".reg .pred p;\n"
        ".reg .u32 n;\n"
        "mbarrier.try_wait.parity.shared::cta.b64 p, [%0], %1;\n"
        "@p bra DONE;\n"
        "mov.u32 n, 0;\n"
        "LAB_WAIT:\n"
        "mbarrier.try_wait.parity.shared::cta.b64 p, [%0], %1;\n"
        "@p bra DONE;\n"
        "add.u32 n, n, 1;\n"
        "setp.lt.u32 p, n, 4194304;\n"
        "@p bra LAB_WAIT;\n"
        "trap;\n"
        "DONE:\n"
        "}\n" ::"r"(bar), "r"(parity) : "memory");
}
__device__ __forceinline__ void tma_load(uint32_t dst, const CUtensorMap* m, uint32_t bar, int c0, int c1) {
    asm volatile("cp.async.bulk.tensor.2d.shared::cluster.global.mbarrier::complete_tx::bytes [%0], [%1, {%3, %4}], [%2];"
                 ::"r"(dst), "l"(m), "r"(bar), "r"(c0), "r"(c1) : "memory");
}
__device__ __forceinline__ void tma_load_l0(uint32_t dst, const CUtensorMap* m, uint32_t bar, int c0, int c1) {
    asm volatile("{\n.reg .pred p;\n.reg .u32 l;\nmov.u32 l, %%laneid;\nsetp.eq.u32 p, l, 0;\n"
                 "@p cp.async.bulk.tensor.2d.shared::cluster.global.mbarrier::complete_tx::bytes [%0], [%1, {%3, %4}], [%2];\n}"
                 ::"r"(dst), "l"(m), "r"(bar), "r"(c0), "r"(c1) : "memory");
}
__device__ __forceinline__ void mbar_expect_tx_l0(uint32_t bar, uint32_t bytes) {
    asm volatile("{\n.reg .pred p;\n.reg .u32 l;\nmov.u32 l, %%laneid;\nsetp.eq.u32 p, l, 0;\n"
                 "@p mbarrier.arrive.expect_tx.shared::cta.b64 _, [%0], %1;\n}" ::"r"(bar), "r"(bytes) : "memory");
}
__device__ __forceinline__ void tma_store(const CUtensorMap* m, uint32_t src, int c0, int c1) {
    asm volatile("cp.async.bulk.tensor.2d.global.shared::cta.bulk_group [%0, {%2, %3}], [%1];"
                 ::"l"(m), "r"(src), "r"(c0), "r"(c1) : "memory");
}
__device__ __forceinline__ void bulk_commit() { asm volatile("cp.async.bulk.commit_group;" ::: "memory"); }
template <int N> __device__ __forceinline__ void bulk_wait_read() { asm volatile("cp.async.bulk.wait_group.read %0;" ::"n"(N) : "memory"); }
template <int N> __device__ __forceinline__ void bulk_wait() { asm volatile("cp.async.bulk.wait_group %0;" ::"n"(N) : "memory"); }
__device__ __forceinline__ void prefetch_tmap(const CUtensorMap* m) { asm volatile("prefetch.tensormap [%0];" ::"l"(m) : "memory"); }
__device__ __forceinline__ void fence_async_smem() { asm volatile("fence.proxy.async.shared::cta;" ::: "memory"); }
__device__ __forceinline__ void fence_mbar_init() { asm volatile("fence.mbarrier_init.release.cluster;" ::: "memory"); }
__device__ __forceinline__ void bar_sync(int id, int n) { asm volatile("bar.sync %0, %1;" ::"r"(id), "r"(n) : "memory"); }
__device__ __forceinline__ void bar_arrive(int id, int n) { asm volatile("bar.arrive %0, %1;" ::"r"(id), "r"(n) : "memory"); }
__device__ __forceinline__ void pdl_wait() { asm volatile("griddepcontrol.wait;" ::: "memory"); }
__device__ __forceinline__ void pdl_launch() { asm volatile("griddepcontrol.launch_dependents;" ::: "memory"); }
template <int R> __device__ __forceinline__ void reg_inc() { asm volatile("setmaxnreg.inc.sync.aligned.u32 %0;" ::"n"(R)); }
template <int R> __device__ __forceinline__ void reg_dec() { asm volatile("setmaxnreg.dec.sync.aligned.u32 %0;" ::"n"(R)); }

__device__ __forceinline__ void wg_fence() { asm volatile("wgmma.fence.sync.aligned;" ::: "memory"); }
__device__ __forceinline__ void wg_commit() { asm volatile("wgmma.commit_group.sync.aligned;" ::: "memory"); }
template <int N> __device__ __forceinline__ void wg_wait() { asm volatile("wgmma.wait_group.sync.aligned %0;" ::"n"(N) : "memory"); }
template <int N> __device__ __forceinline__ void fence_regs(float* d) {
#pragma unroll
    for (int i = 0; i < N; i++) asm volatile("" : "+f"(d[i])::"memory");
}
template <int N> __device__ __forceinline__ void fence_regs_u(uint32_t* d) {
#pragma unroll
    for (int i = 0; i < N; i++) asm volatile("" : "+r"(d[i])::"memory");
}
__device__ __forceinline__ uint32_t desc_lo(uint32_t addr, uint32_t lbo) { return ((addr & 0x3FFFF) >> 4) | ((lbo >> 4) << 16); }
__device__ __forceinline__ bool elect_one() {
    uint32_t p;
    asm volatile("{\n.reg .pred p;\nelect.sync _|p, 0xffffffff;\nselp.u32 %0, 1, 0, p;\n}" : "=r"(p));
    return p != 0;
}
__device__ __forceinline__ void mbar_arrive_lane0(uint32_t bar) {
    asm volatile("{\n.reg .pred p;\n.reg .u32 l;\nmov.u32 l, %%laneid;\nsetp.eq.u32 p, l, 0;\n@p mbarrier.arrive.shared::cta.b64 _, [%0];\n}" ::"r"(bar) : "memory");
}
__device__ __forceinline__ uint32_t pack_bf16(float lo, float hi) {
    uint32_t r;
    asm("cvt.rn.bf16x2.f32 %0, %1, %2;" : "=r"(r) : "f"(hi), "f"(lo));
    return r;
}
__device__ __forceinline__ void stsm_x4(uint32_t addr, uint32_t r0, uint32_t r1, uint32_t r2, uint32_t r3) {
    asm volatile("stmatrix.sync.aligned.m8n8.x4.shared.b16 [%0], {%1, %2, %3, %4};" ::"r"(addr), "r"(r0), "r"(r1), "r"(r2), "r"(r3) : "memory");
}
__device__ __forceinline__ void ldsm_x4(uint32_t addr, uint32_t& r0, uint32_t& r1, uint32_t& r2, uint32_t& r3) {
    asm volatile("ldmatrix.sync.aligned.m8n8.x4.shared.b16 {%0, %1, %2, %3}, [%4];" : "=r"(r0), "=r"(r1), "=r"(r2), "=r"(r3) : "r"(addr) : "memory");
}
__device__ __forceinline__ float nanmax(float a, float b) {
    float r;
    asm("max.NaN.f32 %0, %1, %2;" : "=f"(r) : "f"(a), "f"(b));
    return r;
}
__device__ __forceinline__ float ex2(float x) {
    float y;
    asm("ex2.approx.ftz.f32 %0, %1;" : "=f"(y) : "f"(x));
    return y;
}
__device__ __forceinline__ float ex2_poly(float x) {
    float t = x + 12582912.f;
    float r = t - 12582912.f;
    float f = x - r;
    float p = fmaf(0.055171772837638855f, f, 0.2426113784313202f);
    p = fmaf(p, f, 0.6932609677314758f);
    p = fmaf(p, f, 0.9999279975891113f);
    return __int_as_float(__float_as_int(p) + (__float_as_int(t) << 23));
}

struct TrueT { static constexpr bool value = true; };
struct FalseT { static constexpr bool value = false; };

__device__ __forceinline__ void wg_ss128_z(float* d, uint32_t da, uint32_t db) {
    asm volatile("{\n.reg .b64 da, db;\nmov.b64 da, {%64, 0x40000040};\nmov.b64 db, {%65, 0x40000040};\n"
        "wgmma.mma_async.sync.aligned.m64n128k16.f32.bf16.bf16 {%0, %1, %2, %3, %4, %5, %6, %7, %8, %9, %10, %11, %12, %13, %14, %15, %16, %17, %18, %19, %20, %21, %22, %23, %24, %25, %26, %27, %28, %29, %30, %31, %32, %33, %34, %35, %36, %37, %38, %39, %40, %41, %42, %43, %44, %45, %46, %47, %48, %49, %50, %51, %52, %53, %54, %55, %56, %57, %58, %59, %60, %61, %62, %63}, da, db, 0, 1, 1, 0, 1;\n}"
        : "=f"(d[0]), "=f"(d[1]), "=f"(d[2]), "=f"(d[3]), "=f"(d[4]), "=f"(d[5]), "=f"(d[6]), "=f"(d[7]), "=f"(d[8]), "=f"(d[9]), "=f"(d[10]), "=f"(d[11]), "=f"(d[12]), "=f"(d[13]), "=f"(d[14]), "=f"(d[15]), "=f"(d[16]), "=f"(d[17]), "=f"(d[18]), "=f"(d[19]), "=f"(d[20]), "=f"(d[21]), "=f"(d[22]), "=f"(d[23]), "=f"(d[24]), "=f"(d[25]), "=f"(d[26]), "=f"(d[27]), "=f"(d[28]), "=f"(d[29]), "=f"(d[30]), "=f"(d[31]), "=f"(d[32]), "=f"(d[33]), "=f"(d[34]), "=f"(d[35]), "=f"(d[36]), "=f"(d[37]), "=f"(d[38]), "=f"(d[39]), "=f"(d[40]), "=f"(d[41]), "=f"(d[42]), "=f"(d[43]), "=f"(d[44]), "=f"(d[45]), "=f"(d[46]), "=f"(d[47]), "=f"(d[48]), "=f"(d[49]), "=f"(d[50]), "=f"(d[51]), "=f"(d[52]), "=f"(d[53]), "=f"(d[54]), "=f"(d[55]), "=f"(d[56]), "=f"(d[57]), "=f"(d[58]), "=f"(d[59]), "=f"(d[60]), "=f"(d[61]), "=f"(d[62]), "=f"(d[63]) : "r"(da), "r"(db));
}
__device__ __forceinline__ void wg_ss128(float* d, uint32_t da, uint32_t db) {
    asm volatile("{\n.reg .b64 da, db;\nmov.b64 da, {%64, 0x40000040};\nmov.b64 db, {%65, 0x40000040};\n"
        "wgmma.mma_async.sync.aligned.m64n128k16.f32.bf16.bf16 {%0, %1, %2, %3, %4, %5, %6, %7, %8, %9, %10, %11, %12, %13, %14, %15, %16, %17, %18, %19, %20, %21, %22, %23, %24, %25, %26, %27, %28, %29, %30, %31, %32, %33, %34, %35, %36, %37, %38, %39, %40, %41, %42, %43, %44, %45, %46, %47, %48, %49, %50, %51, %52, %53, %54, %55, %56, %57, %58, %59, %60, %61, %62, %63}, da, db, 1, 1, 1, 0, 1;\n}"
        : "+f"(d[0]), "+f"(d[1]), "+f"(d[2]), "+f"(d[3]), "+f"(d[4]), "+f"(d[5]), "+f"(d[6]), "+f"(d[7]), "+f"(d[8]), "+f"(d[9]), "+f"(d[10]), "+f"(d[11]), "+f"(d[12]), "+f"(d[13]), "+f"(d[14]), "+f"(d[15]), "+f"(d[16]), "+f"(d[17]), "+f"(d[18]), "+f"(d[19]), "+f"(d[20]), "+f"(d[21]), "+f"(d[22]), "+f"(d[23]), "+f"(d[24]), "+f"(d[25]), "+f"(d[26]), "+f"(d[27]), "+f"(d[28]), "+f"(d[29]), "+f"(d[30]), "+f"(d[31]), "+f"(d[32]), "+f"(d[33]), "+f"(d[34]), "+f"(d[35]), "+f"(d[36]), "+f"(d[37]), "+f"(d[38]), "+f"(d[39]), "+f"(d[40]), "+f"(d[41]), "+f"(d[42]), "+f"(d[43]), "+f"(d[44]), "+f"(d[45]), "+f"(d[46]), "+f"(d[47]), "+f"(d[48]), "+f"(d[49]), "+f"(d[50]), "+f"(d[51]), "+f"(d[52]), "+f"(d[53]), "+f"(d[54]), "+f"(d[55]), "+f"(d[56]), "+f"(d[57]), "+f"(d[58]), "+f"(d[59]), "+f"(d[60]), "+f"(d[61]), "+f"(d[62]), "+f"(d[63]) : "r"(da), "r"(db));
}
__device__ __forceinline__ void wg_ss192_z(float* d, uint32_t da, uint32_t db) {
    asm volatile("{\n.reg .b64 da, db;\nmov.b64 da, {%96, 0x40000040};\nmov.b64 db, {%97, 0x40000040};\n"
        "wgmma.mma_async.sync.aligned.m64n192k16.f32.bf16.bf16 {%0, %1, %2, %3, %4, %5, %6, %7, %8, %9, %10, %11, %12, %13, %14, %15, %16, %17, %18, %19, %20, %21, %22, %23, %24, %25, %26, %27, %28, %29, %30, %31, %32, %33, %34, %35, %36, %37, %38, %39, %40, %41, %42, %43, %44, %45, %46, %47, %48, %49, %50, %51, %52, %53, %54, %55, %56, %57, %58, %59, %60, %61, %62, %63, %64, %65, %66, %67, %68, %69, %70, %71, %72, %73, %74, %75, %76, %77, %78, %79, %80, %81, %82, %83, %84, %85, %86, %87, %88, %89, %90, %91, %92, %93, %94, %95}, da, db, 0, 1, 1, 0, 1;\n}"
        : "=f"(d[0]), "=f"(d[1]), "=f"(d[2]), "=f"(d[3]), "=f"(d[4]), "=f"(d[5]), "=f"(d[6]), "=f"(d[7]), "=f"(d[8]), "=f"(d[9]), "=f"(d[10]), "=f"(d[11]), "=f"(d[12]), "=f"(d[13]), "=f"(d[14]), "=f"(d[15]), "=f"(d[16]), "=f"(d[17]), "=f"(d[18]), "=f"(d[19]), "=f"(d[20]), "=f"(d[21]), "=f"(d[22]), "=f"(d[23]), "=f"(d[24]), "=f"(d[25]), "=f"(d[26]), "=f"(d[27]), "=f"(d[28]), "=f"(d[29]), "=f"(d[30]), "=f"(d[31]), "=f"(d[32]), "=f"(d[33]), "=f"(d[34]), "=f"(d[35]), "=f"(d[36]), "=f"(d[37]), "=f"(d[38]), "=f"(d[39]), "=f"(d[40]), "=f"(d[41]), "=f"(d[42]), "=f"(d[43]), "=f"(d[44]), "=f"(d[45]), "=f"(d[46]), "=f"(d[47]), "=f"(d[48]), "=f"(d[49]), "=f"(d[50]), "=f"(d[51]), "=f"(d[52]), "=f"(d[53]), "=f"(d[54]), "=f"(d[55]), "=f"(d[56]), "=f"(d[57]), "=f"(d[58]), "=f"(d[59]), "=f"(d[60]), "=f"(d[61]), "=f"(d[62]), "=f"(d[63]), "=f"(d[64]), "=f"(d[65]), "=f"(d[66]), "=f"(d[67]), "=f"(d[68]), "=f"(d[69]), "=f"(d[70]), "=f"(d[71]), "=f"(d[72]), "=f"(d[73]), "=f"(d[74]), "=f"(d[75]), "=f"(d[76]), "=f"(d[77]), "=f"(d[78]), "=f"(d[79]), "=f"(d[80]), "=f"(d[81]), "=f"(d[82]), "=f"(d[83]), "=f"(d[84]), "=f"(d[85]), "=f"(d[86]), "=f"(d[87]), "=f"(d[88]), "=f"(d[89]), "=f"(d[90]), "=f"(d[91]), "=f"(d[92]), "=f"(d[93]), "=f"(d[94]), "=f"(d[95]) : "r"(da), "r"(db));
}
__device__ __forceinline__ void wg_ss192(float* d, uint32_t da, uint32_t db) {
    asm volatile("{\n.reg .b64 da, db;\nmov.b64 da, {%96, 0x40000040};\nmov.b64 db, {%97, 0x40000040};\n"
        "wgmma.mma_async.sync.aligned.m64n192k16.f32.bf16.bf16 {%0, %1, %2, %3, %4, %5, %6, %7, %8, %9, %10, %11, %12, %13, %14, %15, %16, %17, %18, %19, %20, %21, %22, %23, %24, %25, %26, %27, %28, %29, %30, %31, %32, %33, %34, %35, %36, %37, %38, %39, %40, %41, %42, %43, %44, %45, %46, %47, %48, %49, %50, %51, %52, %53, %54, %55, %56, %57, %58, %59, %60, %61, %62, %63, %64, %65, %66, %67, %68, %69, %70, %71, %72, %73, %74, %75, %76, %77, %78, %79, %80, %81, %82, %83, %84, %85, %86, %87, %88, %89, %90, %91, %92, %93, %94, %95}, da, db, 1, 1, 1, 0, 1;\n}"
        : "+f"(d[0]), "+f"(d[1]), "+f"(d[2]), "+f"(d[3]), "+f"(d[4]), "+f"(d[5]), "+f"(d[6]), "+f"(d[7]), "+f"(d[8]), "+f"(d[9]), "+f"(d[10]), "+f"(d[11]), "+f"(d[12]), "+f"(d[13]), "+f"(d[14]), "+f"(d[15]), "+f"(d[16]), "+f"(d[17]), "+f"(d[18]), "+f"(d[19]), "+f"(d[20]), "+f"(d[21]), "+f"(d[22]), "+f"(d[23]), "+f"(d[24]), "+f"(d[25]), "+f"(d[26]), "+f"(d[27]), "+f"(d[28]), "+f"(d[29]), "+f"(d[30]), "+f"(d[31]), "+f"(d[32]), "+f"(d[33]), "+f"(d[34]), "+f"(d[35]), "+f"(d[36]), "+f"(d[37]), "+f"(d[38]), "+f"(d[39]), "+f"(d[40]), "+f"(d[41]), "+f"(d[42]), "+f"(d[43]), "+f"(d[44]), "+f"(d[45]), "+f"(d[46]), "+f"(d[47]), "+f"(d[48]), "+f"(d[49]), "+f"(d[50]), "+f"(d[51]), "+f"(d[52]), "+f"(d[53]), "+f"(d[54]), "+f"(d[55]), "+f"(d[56]), "+f"(d[57]), "+f"(d[58]), "+f"(d[59]), "+f"(d[60]), "+f"(d[61]), "+f"(d[62]), "+f"(d[63]), "+f"(d[64]), "+f"(d[65]), "+f"(d[66]), "+f"(d[67]), "+f"(d[68]), "+f"(d[69]), "+f"(d[70]), "+f"(d[71]), "+f"(d[72]), "+f"(d[73]), "+f"(d[74]), "+f"(d[75]), "+f"(d[76]), "+f"(d[77]), "+f"(d[78]), "+f"(d[79]), "+f"(d[80]), "+f"(d[81]), "+f"(d[82]), "+f"(d[83]), "+f"(d[84]), "+f"(d[85]), "+f"(d[86]), "+f"(d[87]), "+f"(d[88]), "+f"(d[89]), "+f"(d[90]), "+f"(d[91]), "+f"(d[92]), "+f"(d[93]), "+f"(d[94]), "+f"(d[95]) : "r"(da), "r"(db));
}
__device__ __forceinline__ void wg_ss256_z(float* d, uint32_t da, uint32_t db) {
    asm volatile("{\n.reg .b64 da, db;\nmov.b64 da, {%128, 0x40000040};\nmov.b64 db, {%129, 0x40000040};\n"
        "wgmma.mma_async.sync.aligned.m64n256k16.f32.bf16.bf16 {%0, %1, %2, %3, %4, %5, %6, %7, %8, %9, %10, %11, %12, %13, %14, %15, %16, %17, %18, %19, %20, %21, %22, %23, %24, %25, %26, %27, %28, %29, %30, %31, %32, %33, %34, %35, %36, %37, %38, %39, %40, %41, %42, %43, %44, %45, %46, %47, %48, %49, %50, %51, %52, %53, %54, %55, %56, %57, %58, %59, %60, %61, %62, %63, %64, %65, %66, %67, %68, %69, %70, %71, %72, %73, %74, %75, %76, %77, %78, %79, %80, %81, %82, %83, %84, %85, %86, %87, %88, %89, %90, %91, %92, %93, %94, %95, %96, %97, %98, %99, %100, %101, %102, %103, %104, %105, %106, %107, %108, %109, %110, %111, %112, %113, %114, %115, %116, %117, %118, %119, %120, %121, %122, %123, %124, %125, %126, %127}, da, db, 0, 1, 1, 0, 1;\n}"
        : "=f"(d[0]), "=f"(d[1]), "=f"(d[2]), "=f"(d[3]), "=f"(d[4]), "=f"(d[5]), "=f"(d[6]), "=f"(d[7]), "=f"(d[8]), "=f"(d[9]), "=f"(d[10]), "=f"(d[11]), "=f"(d[12]), "=f"(d[13]), "=f"(d[14]), "=f"(d[15]), "=f"(d[16]), "=f"(d[17]), "=f"(d[18]), "=f"(d[19]), "=f"(d[20]), "=f"(d[21]), "=f"(d[22]), "=f"(d[23]), "=f"(d[24]), "=f"(d[25]), "=f"(d[26]), "=f"(d[27]), "=f"(d[28]), "=f"(d[29]), "=f"(d[30]), "=f"(d[31]), "=f"(d[32]), "=f"(d[33]), "=f"(d[34]), "=f"(d[35]), "=f"(d[36]), "=f"(d[37]), "=f"(d[38]), "=f"(d[39]), "=f"(d[40]), "=f"(d[41]), "=f"(d[42]), "=f"(d[43]), "=f"(d[44]), "=f"(d[45]), "=f"(d[46]), "=f"(d[47]), "=f"(d[48]), "=f"(d[49]), "=f"(d[50]), "=f"(d[51]), "=f"(d[52]), "=f"(d[53]), "=f"(d[54]), "=f"(d[55]), "=f"(d[56]), "=f"(d[57]), "=f"(d[58]), "=f"(d[59]), "=f"(d[60]), "=f"(d[61]), "=f"(d[62]), "=f"(d[63]), "=f"(d[64]), "=f"(d[65]), "=f"(d[66]), "=f"(d[67]), "=f"(d[68]), "=f"(d[69]), "=f"(d[70]), "=f"(d[71]), "=f"(d[72]), "=f"(d[73]), "=f"(d[74]), "=f"(d[75]), "=f"(d[76]), "=f"(d[77]), "=f"(d[78]), "=f"(d[79]), "=f"(d[80]), "=f"(d[81]), "=f"(d[82]), "=f"(d[83]), "=f"(d[84]), "=f"(d[85]), "=f"(d[86]), "=f"(d[87]), "=f"(d[88]), "=f"(d[89]), "=f"(d[90]), "=f"(d[91]), "=f"(d[92]), "=f"(d[93]), "=f"(d[94]), "=f"(d[95]), "=f"(d[96]), "=f"(d[97]), "=f"(d[98]), "=f"(d[99]), "=f"(d[100]), "=f"(d[101]), "=f"(d[102]), "=f"(d[103]), "=f"(d[104]), "=f"(d[105]), "=f"(d[106]), "=f"(d[107]), "=f"(d[108]), "=f"(d[109]), "=f"(d[110]), "=f"(d[111]), "=f"(d[112]), "=f"(d[113]), "=f"(d[114]), "=f"(d[115]), "=f"(d[116]), "=f"(d[117]), "=f"(d[118]), "=f"(d[119]), "=f"(d[120]), "=f"(d[121]), "=f"(d[122]), "=f"(d[123]), "=f"(d[124]), "=f"(d[125]), "=f"(d[126]), "=f"(d[127]) : "r"(da), "r"(db));
}
__device__ __forceinline__ void wg_ss256(float* d, uint32_t da, uint32_t db) {
    asm volatile("{\n.reg .b64 da, db;\nmov.b64 da, {%128, 0x40000040};\nmov.b64 db, {%129, 0x40000040};\n"
        "wgmma.mma_async.sync.aligned.m64n256k16.f32.bf16.bf16 {%0, %1, %2, %3, %4, %5, %6, %7, %8, %9, %10, %11, %12, %13, %14, %15, %16, %17, %18, %19, %20, %21, %22, %23, %24, %25, %26, %27, %28, %29, %30, %31, %32, %33, %34, %35, %36, %37, %38, %39, %40, %41, %42, %43, %44, %45, %46, %47, %48, %49, %50, %51, %52, %53, %54, %55, %56, %57, %58, %59, %60, %61, %62, %63, %64, %65, %66, %67, %68, %69, %70, %71, %72, %73, %74, %75, %76, %77, %78, %79, %80, %81, %82, %83, %84, %85, %86, %87, %88, %89, %90, %91, %92, %93, %94, %95, %96, %97, %98, %99, %100, %101, %102, %103, %104, %105, %106, %107, %108, %109, %110, %111, %112, %113, %114, %115, %116, %117, %118, %119, %120, %121, %122, %123, %124, %125, %126, %127}, da, db, 1, 1, 1, 0, 1;\n}"
        : "+f"(d[0]), "+f"(d[1]), "+f"(d[2]), "+f"(d[3]), "+f"(d[4]), "+f"(d[5]), "+f"(d[6]), "+f"(d[7]), "+f"(d[8]), "+f"(d[9]), "+f"(d[10]), "+f"(d[11]), "+f"(d[12]), "+f"(d[13]), "+f"(d[14]), "+f"(d[15]), "+f"(d[16]), "+f"(d[17]), "+f"(d[18]), "+f"(d[19]), "+f"(d[20]), "+f"(d[21]), "+f"(d[22]), "+f"(d[23]), "+f"(d[24]), "+f"(d[25]), "+f"(d[26]), "+f"(d[27]), "+f"(d[28]), "+f"(d[29]), "+f"(d[30]), "+f"(d[31]), "+f"(d[32]), "+f"(d[33]), "+f"(d[34]), "+f"(d[35]), "+f"(d[36]), "+f"(d[37]), "+f"(d[38]), "+f"(d[39]), "+f"(d[40]), "+f"(d[41]), "+f"(d[42]), "+f"(d[43]), "+f"(d[44]), "+f"(d[45]), "+f"(d[46]), "+f"(d[47]), "+f"(d[48]), "+f"(d[49]), "+f"(d[50]), "+f"(d[51]), "+f"(d[52]), "+f"(d[53]), "+f"(d[54]), "+f"(d[55]), "+f"(d[56]), "+f"(d[57]), "+f"(d[58]), "+f"(d[59]), "+f"(d[60]), "+f"(d[61]), "+f"(d[62]), "+f"(d[63]), "+f"(d[64]), "+f"(d[65]), "+f"(d[66]), "+f"(d[67]), "+f"(d[68]), "+f"(d[69]), "+f"(d[70]), "+f"(d[71]), "+f"(d[72]), "+f"(d[73]), "+f"(d[74]), "+f"(d[75]), "+f"(d[76]), "+f"(d[77]), "+f"(d[78]), "+f"(d[79]), "+f"(d[80]), "+f"(d[81]), "+f"(d[82]), "+f"(d[83]), "+f"(d[84]), "+f"(d[85]), "+f"(d[86]), "+f"(d[87]), "+f"(d[88]), "+f"(d[89]), "+f"(d[90]), "+f"(d[91]), "+f"(d[92]), "+f"(d[93]), "+f"(d[94]), "+f"(d[95]), "+f"(d[96]), "+f"(d[97]), "+f"(d[98]), "+f"(d[99]), "+f"(d[100]), "+f"(d[101]), "+f"(d[102]), "+f"(d[103]), "+f"(d[104]), "+f"(d[105]), "+f"(d[106]), "+f"(d[107]), "+f"(d[108]), "+f"(d[109]), "+f"(d[110]), "+f"(d[111]), "+f"(d[112]), "+f"(d[113]), "+f"(d[114]), "+f"(d[115]), "+f"(d[116]), "+f"(d[117]), "+f"(d[118]), "+f"(d[119]), "+f"(d[120]), "+f"(d[121]), "+f"(d[122]), "+f"(d[123]), "+f"(d[124]), "+f"(d[125]), "+f"(d[126]), "+f"(d[127]) : "r"(da), "r"(db));
}
__device__ __forceinline__ void wg_rs64_z(float* d, uint32_t a0, uint32_t a1, uint32_t a2, uint32_t a3, uint32_t db) {
    asm volatile("{\n.reg .b64 db;\nmov.b64 db, {%36, 0x80000020};\n"
        "wgmma.mma_async.sync.aligned.m64n64k16.f32.bf16.bf16 {%0, %1, %2, %3, %4, %5, %6, %7, %8, %9, %10, %11, %12, %13, %14, %15, %16, %17, %18, %19, %20, %21, %22, %23, %24, %25, %26, %27, %28, %29, %30, %31}, {%32, %33, %34, %35}, db, 0, 1, 1, 0;\n}"
        : "=f"(d[0]), "=f"(d[1]), "=f"(d[2]), "=f"(d[3]), "=f"(d[4]), "=f"(d[5]), "=f"(d[6]), "=f"(d[7]), "=f"(d[8]), "=f"(d[9]), "=f"(d[10]), "=f"(d[11]), "=f"(d[12]), "=f"(d[13]), "=f"(d[14]), "=f"(d[15]), "=f"(d[16]), "=f"(d[17]), "=f"(d[18]), "=f"(d[19]), "=f"(d[20]), "=f"(d[21]), "=f"(d[22]), "=f"(d[23]), "=f"(d[24]), "=f"(d[25]), "=f"(d[26]), "=f"(d[27]), "=f"(d[28]), "=f"(d[29]), "=f"(d[30]), "=f"(d[31]) : "r"(a0), "r"(a1), "r"(a2), "r"(a3), "r"(db));
}
__device__ __forceinline__ void wg_rs64(float* d, uint32_t a0, uint32_t a1, uint32_t a2, uint32_t a3, uint32_t db) {
    asm volatile("{\n.reg .b64 db;\nmov.b64 db, {%36, 0x80000020};\n"
        "wgmma.mma_async.sync.aligned.m64n64k16.f32.bf16.bf16 {%0, %1, %2, %3, %4, %5, %6, %7, %8, %9, %10, %11, %12, %13, %14, %15, %16, %17, %18, %19, %20, %21, %22, %23, %24, %25, %26, %27, %28, %29, %30, %31}, {%32, %33, %34, %35}, db, 1, 1, 1, 0;\n}"
        : "+f"(d[0]), "+f"(d[1]), "+f"(d[2]), "+f"(d[3]), "+f"(d[4]), "+f"(d[5]), "+f"(d[6]), "+f"(d[7]), "+f"(d[8]), "+f"(d[9]), "+f"(d[10]), "+f"(d[11]), "+f"(d[12]), "+f"(d[13]), "+f"(d[14]), "+f"(d[15]), "+f"(d[16]), "+f"(d[17]), "+f"(d[18]), "+f"(d[19]), "+f"(d[20]), "+f"(d[21]), "+f"(d[22]), "+f"(d[23]), "+f"(d[24]), "+f"(d[25]), "+f"(d[26]), "+f"(d[27]), "+f"(d[28]), "+f"(d[29]), "+f"(d[30]), "+f"(d[31]) : "r"(a0), "r"(a1), "r"(a2), "r"(a3), "r"(db));
}
__device__ __forceinline__ void wg_rs40t(float* d, uint32_t a0, uint32_t a1, uint32_t a2, uint32_t a3, uint32_t db) {
    asm volatile("{\n.reg .b64 db;\nmov.b64 db, {%24, 0x80000020};\n"
        "wgmma.mma_async.sync.aligned.m64n40k16.f32.bf16.bf16 {%0, %1, %2, %3, %4, %5, %6, %7, %8, %9, %10, %11, %12, %13, %14, %15, %16, %17, %18, %19}, {%20, %21, %22, %23}, db, 1, 1, 1, 1;\n}"
        : "+f"(d[0]), "+f"(d[1]), "+f"(d[2]), "+f"(d[3]), "+f"(d[4]), "+f"(d[5]), "+f"(d[6]), "+f"(d[7]), "+f"(d[8]), "+f"(d[9]), "+f"(d[10]), "+f"(d[11]), "+f"(d[12]), "+f"(d[13]), "+f"(d[14]), "+f"(d[15]), "+f"(d[16]), "+f"(d[17]), "+f"(d[18]), "+f"(d[19]) : "r"(a0), "r"(a1), "r"(a2), "r"(a3), "r"(db));
}
__device__ __forceinline__ void wg_rs40t_z(float* d, uint32_t a0, uint32_t a1, uint32_t a2, uint32_t a3, uint32_t db) {
    asm volatile("{\n.reg .b64 db;\nmov.b64 db, {%24, 0x80000020};\n"
        "wgmma.mma_async.sync.aligned.m64n40k16.f32.bf16.bf16 {%0, %1, %2, %3, %4, %5, %6, %7, %8, %9, %10, %11, %12, %13, %14, %15, %16, %17, %18, %19}, {%20, %21, %22, %23}, db, 0, 1, 1, 1;\n}"
        : "=f"(d[0]), "=f"(d[1]), "=f"(d[2]), "=f"(d[3]), "=f"(d[4]), "=f"(d[5]), "=f"(d[6]), "=f"(d[7]), "=f"(d[8]), "=f"(d[9]), "=f"(d[10]), "=f"(d[11]), "=f"(d[12]), "=f"(d[13]), "=f"(d[14]), "=f"(d[15]), "=f"(d[16]), "=f"(d[17]), "=f"(d[18]), "=f"(d[19]) : "r"(a0), "r"(a1), "r"(a2), "r"(a3), "r"(db));
}
__device__ __forceinline__ void wg_rs32t_z(float* d, uint32_t a0, uint32_t a1, uint32_t a2, uint32_t a3, uint32_t db) {
    asm volatile("{\n.reg .b64 db;\nmov.b64 db, {%20, 0x80000020};\n"
        "wgmma.mma_async.sync.aligned.m64n32k16.f32.bf16.bf16 {%0, %1, %2, %3, %4, %5, %6, %7, %8, %9, %10, %11, %12, %13, %14, %15}, {%16, %17, %18, %19}, db, 0, 1, 1, 1;\n}"
        : "=f"(d[0]), "=f"(d[1]), "=f"(d[2]), "=f"(d[3]), "=f"(d[4]), "=f"(d[5]), "=f"(d[6]), "=f"(d[7]), "=f"(d[8]), "=f"(d[9]), "=f"(d[10]), "=f"(d[11]), "=f"(d[12]), "=f"(d[13]), "=f"(d[14]), "=f"(d[15]) : "r"(a0), "r"(a1), "r"(a2), "r"(a3), "r"(db));
}
__device__ __forceinline__ void wg_rs32t(float* d, uint32_t a0, uint32_t a1, uint32_t a2, uint32_t a3, uint32_t db) {
    asm volatile("{\n.reg .b64 db;\nmov.b64 db, {%20, 0x80000020};\n"
        "wgmma.mma_async.sync.aligned.m64n32k16.f32.bf16.bf16 {%0, %1, %2, %3, %4, %5, %6, %7, %8, %9, %10, %11, %12, %13, %14, %15}, {%16, %17, %18, %19}, db, 1, 1, 1, 1;\n}"
        : "+f"(d[0]), "+f"(d[1]), "+f"(d[2]), "+f"(d[3]), "+f"(d[4]), "+f"(d[5]), "+f"(d[6]), "+f"(d[7]), "+f"(d[8]), "+f"(d[9]), "+f"(d[10]), "+f"(d[11]), "+f"(d[12]), "+f"(d[13]), "+f"(d[14]), "+f"(d[15]) : "r"(a0), "r"(a1), "r"(a2), "r"(a3), "r"(db));
}
__device__ __forceinline__ void wg_ss40tt(float* d, uint32_t da, uint32_t db) {
    asm volatile("{\n.reg .b64 da, db;\nmov.b64 da, {%20, 0x40000040};\nmov.b64 db, {%21, 0x80000020};\n"
        "wgmma.mma_async.sync.aligned.m64n40k16.f32.bf16.bf16 {%0, %1, %2, %3, %4, %5, %6, %7, %8, %9, %10, %11, %12, %13, %14, %15, %16, %17, %18, %19}, da, db, 1, 1, 1, 1, 1;\n}"
        : "+f"(d[0]), "+f"(d[1]), "+f"(d[2]), "+f"(d[3]), "+f"(d[4]), "+f"(d[5]), "+f"(d[6]), "+f"(d[7]), "+f"(d[8]), "+f"(d[9]), "+f"(d[10]), "+f"(d[11]), "+f"(d[12]), "+f"(d[13]), "+f"(d[14]), "+f"(d[15]), "+f"(d[16]), "+f"(d[17]), "+f"(d[18]), "+f"(d[19]) : "r"(da), "r"(db));
}

constexpr float QSCALE = 0.17677669529663687f * 1.4426950408889634f;

template <int MB, int STAGES> struct QkvCfg {
    static constexpr int BM = 128 * MB;
    static constexpr int A_BYTES = BM * 128;
    static constexpr int B_BYTES = 3 * 8192;
    static constexpr int STAGE = A_BYTES + B_BYTES;
    static constexpr int OFF_STG = STAGES * STAGE;
    static constexpr int OFF_PHI = OFF_STG + 2 * 24576;
    static constexpr int OFF_BAR = OFF_PHI + 4096;
    static constexpr int SMEM = OFF_BAR + 128 + 1024;
    static constexpr int MT = SEQ / BM;
    static constexpr int TPP = MT * 16;
};

template <int MB, int STAGES, int RC, int RP>
__global__ void __launch_bounds__(384, 1)
qkv_gemm_kernel(const __grid_constant__ TMaps tm, int tile_begin, int tile_end, int first_prob) {
    using C = QkvCfg<MB, STAGES>;
    extern __shared__ uint8_t smem_raw[];
    const uint32_t sb = (smem_u32(smem_raw) + 1023) & ~1023u;
    const uint32_t bar_full = sb + C::OFF_BAR, bar_empty = bar_full + 8 * STAGES;
    const uint32_t bar_phi_full = bar_empty + 8 * STAGES, bar_phi_empty = bar_phi_full + 8;
    const int wg = __shfl_sync(0xffffffffu, threadIdx.x >> 7, 0);
    const int warp = __shfl_sync(0xffffffffu, (threadIdx.x >> 5) & 3, 0), lane = threadIdx.x & 31;

    if (threadIdx.x == 0) {
        for (int s = 0; s < STAGES; s++) { mbar_init(bar_full + 8 * s, 1); mbar_init(bar_empty + 8 * s, 8); }
        mbar_init(bar_phi_full, 1);
        mbar_init(bar_phi_empty, 8);
        fence_mbar_init();
    }
    __syncthreads();
    pdl_launch();
    if (threadIdx.x == 0) { TS(0, 0); TSC(5, 0); }

    if (wg == 2) {
        reg_dec<RP>();
        if (warp == 0 && lane == 0) {
            prefetch_tmap(&tm.x[0]); prefetch_tmap(&tm.x[1]); prefetch_tmap(&tm.w[0]); prefetch_tmap(&tm.w[1]);
            int s = 0; uint32_t ph = 1; uint32_t phi_ph = 1;
            for (int t = tile_begin + blockIdx.x; t < tile_end; t += gridDim.x) {
                const int pi = t / C::TPP, tt = t % C::TPP;
                const int prob = pi == 0 ? first_prob : 1 - first_prob;
                const int mt = tt % C::MT, nt = tt / C::MT;
                const CUtensorMap* mx = &tm.x[prob];
                const CUtensorMap* mw = &tm.w[prob];
                for (int kt = 0; kt < 16; kt++) {
                    mbar_wait(bar_empty + 8 * s, ph);
                    const uint32_t st = sb + s * C::STAGE, fb = bar_full + 8 * s;
                    mbar_expect_tx(fb, C::STAGE);
                    tma_load(st, mx, fb, kt * 64, mt * C::BM);
#pragma unroll
                    for (int p = 0; p < 3; p++) tma_load(st + C::A_BYTES + p * 8192, mw, fb, p * 1024 + nt * 64, kt * 64);
                    if (++s == STAGES) { s = 0; ph ^= 1; }
                    if (kt == 2 && prob == 0) {
                        mbar_wait(bar_phi_empty, phi_ph);
                        mbar_expect_tx(bar_phi_full, 4096);
                        tma_load(sb + C::OFF_PHI, &tm.phi, bar_phi_full, 0, nt * 64);
                        phi_ph ^= 1;
                    }
                }
            }
        }
    } else {
        reg_inc<RC>();
        float acc[MB][96];
        int s = 0; uint32_t ph = 0; uint32_t phi_ph = 0;
        for (int t = tile_begin + blockIdx.x; t < tile_end; t += gridDim.x) {
            const int pi = t / C::TPP, tt = t % C::TPP;
            const int prob = pi == 0 ? first_prob : 1 - first_prob;
            const int mt = tt % C::MT, nt = tt / C::MT;
            int prev = 0;
            auto kstep = [&](auto first) {
                mbar_wait(bar_full + 8 * s, ph);
                const uint32_t st = sb + s * C::STAGE;
                const uint32_t dA = desc_lo(st + wg * (64 * MB * 128), 16);
                const uint32_t dB = desc_lo(st + C::A_BYTES, 8192);
                wg_fence();
#pragma unroll
                for (int kk = 0; kk < 4; kk++) {
#pragma unroll
                    for (int mb = 0; mb < MB; mb++) {
                        if (decltype(first)::value && kk == 0) wg_ss192_z(acc[mb], dA + mb * 512 + kk * 2, dB + kk * 128);
                        else wg_ss192(acc[mb], dA + mb * 512 + kk * 2, dB + kk * 128);
                    }
                }
                wg_commit();
                if (!decltype(first)::value) {
                    wg_wait<1>();
                    mbar_arrive_lane0(bar_empty + 8 * prev);
                }
                prev = s;
                if (++s == STAGES) { s = 0; ph ^= 1; }
            };
            kstep(TrueT{});
            if (threadIdx.x == 0) TS(0, t < (int)gridDim.x ? 1 : 4);
#pragma unroll 1
            for (int kt = 1; kt < 16; kt++) kstep(FalseT{});
            wg_wait<0>();
            if (threadIdx.x == 0) TS(0, t < (int)gridDim.x ? 2 : 5);
            mbar_arrive_lane0(bar_empty + 8 * prev);
#pragma unroll
            for (int mb = 0; mb < MB; mb++) fence_regs<96>(acc[mb]);

            uint32_t tidl;
            asm volatile("mov.u32 %0, %%tid.x;" : "=r"(tidl));
            const int lane = tidl & 31;
            const uint32_t stg = sb + C::OFF_STG + (tidl >> 5) * 6144;
            const int strow = (lane & 7) + ((lane >> 3) & 1) * 8;
            const uint32_t st_base = stg + strow * 64;
            const uint32_t st_x = (strow >> 1) & 3, st_c = lane >> 4;
            const uint32_t ld_base = stg + (lane >> 2) * 64 + (((lane & 3) ^ ((lane >> 3) & 3)) << 4);
            if (prob == 0) { mbar_wait(bar_phi_full, phi_ph); phi_ph ^= 1; }
            float nrm[6];
#pragma unroll
            for (int i = 0; i < 6; i++) nrm[i] = 0.f;
#pragma unroll
            for (int mb = 0; mb < MB; mb++) {
                const int tok0 = mt * C::BM + wg * (64 * MB) + mb * 64 + warp * 16;
                float* a = acc[mb];
                auto stage_block = [&](int sbk, const uint32_t* pk) {
                    stsm_x4(st_base + sbk * 1024 + ((st_c ^ st_x) << 4), pk[0], pk[1], pk[2], pk[3]);
                    stsm_x4(st_base + sbk * 1024 + (((2 + st_c) ^ st_x) << 4), pk[4], pk[5], pk[6], pk[7]);
                };
                if (mb > 0) __syncwarp();
                if (prob == 1) {
#pragma unroll
                    for (int p = 0; p < 3; p++) {
#pragma unroll
                        for (int hh = 0; hh < 2; hh++) {
                            float s0 = 0.f, s1 = 0.f;
                            uint32_t pk[8];
#pragma unroll
                            for (int g = 0; g < 4; g++) {
                                const int j = p * 8 + hh * 4 + g;
                                float v0 = a[4 * j], v1 = a[4 * j + 1], v2 = a[4 * j + 2], v3 = a[4 * j + 3];
                                if (p == 0) { v0 *= QSCALE; v1 *= QSCALE; v2 *= QSCALE; v3 *= QSCALE; }
                                if (p < 2) {
                                    s0 = fmaf(v0, v0, s0); s0 = fmaf(v1, v1, s0);
                                    s1 = fmaf(v2, v2, s1); s1 = fmaf(v3, v3, s1);
                                } else {
                                    s0 = nanmax(s0, nanmax(fabsf(v0), fabsf(v1)));
                                    s1 = nanmax(s1, nanmax(fabsf(v2), fabsf(v3)));
                                }
                                pk[2 * g] = pack_bf16(v0, v1); pk[2 * g + 1] = pack_bf16(v2, v3);
                            }
                            nrm[p * 2 + hh] = nanmax(nrm[p * 2 + hh], nanmax(s0, s1));
                            stage_block(p * 2 + hh, pk);
                        }
                    }
                } else {
#pragma unroll
                    for (int hh = 0; hh < 2; hh++) {
                        uint32_t pk[8];
#pragma unroll
                        for (int g = 0; g < 4; g++) {
                            const int j = 16 + hh * 4 + g;
                            pk[2 * g] = pack_bf16(a[4 * j], a[4 * j + 1]); pk[2 * g + 1] = pack_bf16(a[4 * j + 2], a[4 * j + 3]);
                        }
                        stage_block(4 + hh, pk);
                    }
#pragma unroll
                    for (int p = 0; p < 2; p++) {
                        uint32_t fr[16];
                        float f[2][16];
#pragma unroll
                        for (int j = 0; j < 8; j++) {
                            const int jj = p * 8 + j;
                            fr[2 * j] = pack_bf16(a[4 * jj], a[4 * jj + 1]); fr[2 * j + 1] = pack_bf16(a[4 * jj + 2], a[4 * jj + 3]);
                        }
                        fence_regs_u<16>(fr);
                        wg_fence();
#pragma unroll
                        for (int hh = 0; hh < 2; hh++) {
                            const uint32_t dP = desc_lo(sb + C::OFF_PHI + hh * 2048, 16);
                            wg_rs32t_z(f[hh], fr[8 * hh], fr[8 * hh + 1], fr[8 * hh + 2], fr[8 * hh + 3], dP);
                            wg_rs32t(f[hh], fr[8 * hh + 4], fr[8 * hh + 5], fr[8 * hh + 6], fr[8 * hh + 7], dP + 64);
                        }
                        wg_commit();
                        wg_wait<0>();
                        fence_regs<16>(f[0]); fence_regs<16>(f[1]);
#pragma unroll
                        for (int hh = 0; hh < 2; hh++) {
                            uint32_t pk[8];
#pragma unroll
                            for (int g = 0; g < 4; g++) {
                                pk[2 * g] = pack_bf16(f[hh][4 * g], f[hh][4 * g + 1]); pk[2 * g + 1] = pack_bf16(f[hh][4 * g + 2], f[hh][4 * g + 3]);
                            }
                            stage_block(p * 2 + hh, pk);
                        }
                    }
                    if (mb == MB - 1) mbar_arrive_lane0(bar_phi_empty);
                }
                __syncwarp();
#pragma unroll
                for (int sbk = 0; sbk < 6; sbk++) {
                    const int p = sbk >> 1, hh = sbk & 1;
                    uint4* dst = reinterpret_cast<uint4*>(g_qkv + ((size_t)((prob * 3 + p) * NH + nt * 2 + hh) * SEQ + tok0) * 32) + lane;
#pragma unroll
                    for (int i = 0; i < 2; i++) {
                        uint4 v;
                        asm volatile("ld.shared.v4.b32 {%0, %1, %2, %3}, [%4];" : "=r"(v.x), "=r"(v.y), "=r"(v.z), "=r"(v.w) : "r"(ld_base + sbk * 1024 + i * 512) : "memory");
                        dst[i * 32] = v;
                    }
                }
            }
            if (prob == 1) {
#pragma unroll
                for (int o = 4; o < 32; o <<= 1) {
#pragma unroll
                    for (int i = 0; i < 6; i++) nrm[i] = nanmax(nrm[i], __shfl_xor_sync(0xffffffffu, nrm[i], o));
                }
#pragma unroll
                for (int o = 1; o < 4; o <<= 1) {
#pragma unroll
                    for (int i = 0; i < 6; i++) {
                        const float other = __shfl_xor_sync(0xffffffffu, nrm[i], o);
                        nrm[i] = i < 4 ? nrm[i] + other : nanmax(nrm[i], other);
                    }
                }
                if (lane < 6 * MB) {
                    const int i = lane / MB, sl = lane % MB;
                    float v = nrm[0];
#pragma unroll
                    for (int q = 1; q < 6; q++) v = i == q ? nrm[q] : v;
                    g_norm[((i >> 1) * NH + nt * 2 + (i & 1)) * 128 + (mt * 8 + wg * 4 + warp) * MB + sl] = v;
                }
            }
            if (threadIdx.x == 0) TS(0, t < (int)gridDim.x ? 3 : 6);
        }
        if (threadIdx.x == 0) { TS(0, 7); TSC(5, 1); }
    }
}

template <int BN, int STAGES> struct OutCfg {
    static constexpr int A_BYTES = 128 * 128;
    static constexpr int B_BYTES = (BN / 64) * 8192;
    static constexpr int STAGE = A_BYTES + B_BYTES;
    static constexpr int OFF_BAR = STAGES * STAGE;
    static constexpr int SMEM = OFF_BAR + 128 + 1024;
    static constexpr int NT = DM / BN;
};

template <int BN> __device__ __forceinline__ void wg_ss_z(float* d, uint32_t a, uint32_t b);
template <> __device__ __forceinline__ void wg_ss_z<128>(float* d, uint32_t a, uint32_t b) { wg_ss128_z(d, a, b); }
template <> __device__ __forceinline__ void wg_ss_z<256>(float* d, uint32_t a, uint32_t b) { wg_ss256_z(d, a, b); }
template <int BN> __device__ __forceinline__ void wg_ss(float* d, uint32_t a, uint32_t b);
template <> __device__ __forceinline__ void wg_ss<128>(float* d, uint32_t a, uint32_t b) { wg_ss128(d, a, b); }
template <> __device__ __forceinline__ void wg_ss<256>(float* d, uint32_t a, uint32_t b) { wg_ss256(d, a, b); }

template <int BN, int STAGES, int RC, int RP>
__global__ void __launch_bounds__(384, 1)
out_gemm_kernel(const __grid_constant__ TMaps tm, int prob_begin) {
    using C = OutCfg<BN, STAGES>;
    extern __shared__ uint8_t smem_raw[];
    const uint32_t sb = (smem_u32(smem_raw) + 1023) & ~1023u;
    const uint32_t bar_full = sb + C::OFF_BAR, bar_empty = bar_full + 8 * STAGES;
    const int wg = __shfl_sync(0xffffffffu, threadIdx.x >> 7, 0);
    const int warp = __shfl_sync(0xffffffffu, (threadIdx.x >> 5) & 3, 0), lane = threadIdx.x & 31;
    const int t = blockIdx.x;
    const int prob = prob_begin + t / (16 * C::NT);
    const int mt = (t % (16 * C::NT)) % 16, nt = (t % (16 * C::NT)) / 16;

    if (threadIdx.x == 0) {
        for (int s = 0; s < STAGES; s++) { mbar_init(bar_full + 8 * s, 1); mbar_init(bar_empty + 8 * s, 8); }
        fence_mbar_init();
    }
    __syncthreads();

    if (threadIdx.x == 0) TS(4, 0);
    if (wg == 2) {
        reg_dec<RP>();
        if (warp == 0 && lane == 0) {
            const CUtensorMap* mw = &tm.wo[prob];
            prefetch_tmap(mw); prefetch_tmap(&tm.o); prefetch_tmap(&tm.out);
#pragma unroll
            for (int s = 0; s < STAGES; s++) {
                const uint32_t st = sb + s * C::STAGE, fb = bar_full + 8 * s;
                mbar_expect_tx(fb, C::STAGE);
#pragma unroll
                for (int p = 0; p < BN / 64; p++) tma_load(st + C::A_BYTES + p * 8192, mw, fb, nt * BN + p * 64, s * 64);
            }
            pdl_wait();
            TS(4, 1);
#pragma unroll
            for (int s = 0; s < STAGES; s++) tma_load(sb + s * C::STAGE, &tm.o, bar_full + 8 * s, s * 64, prob * SEQ + mt * 128);
            int s = 0; uint32_t ph = 0;
            for (int kt = STAGES; kt < 16; kt++) {
                mbar_wait(bar_empty + 8 * s, ph);
                const uint32_t st = sb + s * C::STAGE, fb = bar_full + 8 * s;
                mbar_expect_tx(fb, C::STAGE);
                tma_load(st, &tm.o, fb, kt * 64, prob * SEQ + mt * 128);
#pragma unroll
                for (int p = 0; p < BN / 64; p++) tma_load(st + C::A_BYTES + p * 8192, mw, fb, nt * BN + p * 64, kt * 64);
                if (++s == STAGES) { s = 0; ph ^= 1; }
            }
        }
    } else {
        reg_inc<RC>();
        float acc[BN / 2];
        int s = 0; uint32_t ph = 0; int prev = 0;
        auto kstep = [&](auto first) {
            mbar_wait(bar_full + 8 * s, ph);
            const uint32_t st = sb + s * C::STAGE;
            const uint32_t dA = desc_lo(st + wg * (64 * 128), 16);
            const uint32_t dB = desc_lo(st + C::A_BYTES, 8192);
            wg_fence();
#pragma unroll
            for (int kk = 0; kk < 4; kk++) {
                if (decltype(first)::value && kk == 0) wg_ss_z<BN>(acc, dA + kk * 2, dB + kk * 128);
                else wg_ss<BN>(acc, dA + kk * 2, dB + kk * 128);
            }
            wg_commit();
            if (!decltype(first)::value) {
                wg_wait<1>();
                mbar_arrive_lane0(bar_empty + 8 * prev);
            }
            prev = s;
            if (++s == STAGES) { s = 0; ph ^= 1; }
        };
        kstep(TrueT{});
        if (threadIdx.x == 0) TS(4, 2);
#pragma unroll 1
        for (int kt = 1; kt < 16; kt++) kstep(FalseT{});
        wg_wait<0>();
        if (threadIdx.x == 0) TS(4, 3);
        fence_regs<BN / 2>(acc);
        bar_sync(3, 256);
        const uint32_t stg = sb + wg * (BN / 64) * 8192;
        const int strow = warp * 16 + (lane & 7) + ((lane >> 3) & 1) * 8;
        const uint32_t st_base = stg + strow * 128;
        const uint32_t st_x = strow & 7, st_c = lane >> 4;
#pragma unroll
        for (int b = 0; b < BN / 64; b++) {
#pragma unroll
            for (int jj = 0; jj < 4; jj++) {
                const int j = b * 8 + jj * 2;
                stsm_x4(st_base + b * 8192 + (((jj * 2 + st_c) ^ st_x) << 4),
                        pack_bf16(acc[4 * j], acc[4 * j + 1]), pack_bf16(acc[4 * j + 2], acc[4 * j + 3]),
                        pack_bf16(acc[4 * j + 4], acc[4 * j + 5]), pack_bf16(acc[4 * j + 6], acc[4 * j + 7]));
            }
        }
        fence_async_smem();
        bar_sync(1 + wg, 128);
        if (warp == 0 && lane == 0) {
#pragma unroll
            for (int b = 0; b < BN / 64; b++) tma_store(&tm.out, stg + b * 8192, prob * DM + nt * BN + b * 64, mt * 128 + wg * 64);
            bulk_commit();
            bulk_wait<0>();
            if (threadIdx.x == 0) TS(4, 4);
        }
    }
}

template <int MASK8> __device__ __forceinline__ void exp_pack8(const float* s, uint32_t* p) {
#pragma unroll
    for (int i = 0; i < 4; i++) {
        float a = s[2 * i], b = s[2 * i + 1];
        a = ((MASK8 >> (2 * i)) & 1) ? ex2_poly(a) : ex2(a);
        b = ((MASK8 >> (2 * i + 1)) & 1) ? ex2_poly(b) : ex2(b);
        p[i] = pack_bf16(a, b);
    }
}

template <int NWG, int KVST> struct AttCfg {
    static constexpr int THREADS = NWG * 128;
    static constexpr int QROWS = NWG * 64;
    static constexpr int KV_STAGE = 16384;
    static constexpr int OFF_Q = KVST * KV_STAGE;
    static constexpr int OFF_ONES = OFF_Q + 2 * QROWS * 64;
    static constexpr int OFF_BAR = OFF_ONES + 1024;
    static constexpr int SMEM = OFF_BAR + 256 + 1024;
    static constexpr int NTASK = NH * (SEQ / QROWS);
};

constexpr float SAFE_BOUND = 90.0f;

template <int NWG, int KVST, int MASK16, int W1, int MINB>
__global__ void __launch_bounds__(NWG * 128, MINB)
attn_kernel(const __grid_constant__ TMaps tm) {
    using C = AttCfg<NWG, KVST>;
    extern __shared__ uint8_t smem_raw[];
    const uint32_t sb = (smem_u32(smem_raw) + 1023) & ~1023u;
    const uint32_t bar_full = sb + C::OFF_BAR, bar_empty = bar_full + 8 * KVST;
    const uint32_t bar_qfull = bar_empty + 8 * KVST, bar_qempty = bar_qfull + 16;
    const int wg = __shfl_sync(0xffffffffu, threadIdx.x >> 7, 0);
    const int warp = __shfl_sync(0xffffffffu, (threadIdx.x >> 5) & 3, 0), lane = threadIdx.x & 31;

    if (threadIdx.x == 0) {
        for (int s = 0; s < KVST; s++) { mbar_init(bar_full + 8 * s, 1); mbar_init(bar_empty + 8 * s, NWG * 4); }
        for (int s = 0; s < 2; s++) { mbar_init(bar_qfull + 8 * s, 1); mbar_init(bar_qempty + 8 * s, NWG * 4); }
        fence_mbar_init();
        prefetch_tmap(&tm.qkv128);
    }
    if (threadIdx.x < 64) {
        asm volatile("st.shared.v4.b32 [%0], {%1, %2, %2, %2};" ::"r"(sb + C::OFF_ONES + threadIdx.x * 16), "r"(0x00003F80u), "r"(0u) : "memory");
        fence_async_smem();
    }
    __syncthreads();
    pdl_launch();
    pdl_wait();
    if (threadIdx.x == 0) TS(3, 0);

    int pr_s = 0, pr_qs = 0, pr_st = 0, pr_t = blockIdx.x;
    uint32_t pr_ph = 1, pr_qph = 1;
    const bool is_prod = (wg == 0 && warp == 0);
    auto produce = [&]() {
        if (pr_t < C::NTASK) {
            if (is_prod) {
                const int h = pr_t / (SEQ / C::QROWS), qt = pr_t % (SEQ / C::QROWS);
                if (pr_st == 0) {
                    mbar_wait(bar_qempty + 8 * pr_qs, pr_qph);
                    mbar_expect_tx_l0(bar_qfull + 8 * pr_qs, C::QROWS * 64);
                    const int rowQ = ((3 + 0) * NH + h) * SEQ + qt * C::QROWS;
#pragma unroll
                    for (int i = 0; i < C::QROWS / 128; i++)
                        tma_load_l0(sb + C::OFF_Q + pr_qs * C::QROWS * 64 + i * 8192, &tm.qkv128, bar_qfull + 8 * pr_qs, 0, rowQ + i * 128);
                }
                mbar_wait(bar_empty + 8 * pr_s, pr_ph);
                const uint32_t dst = sb + pr_s * C::KV_STAGE, fb = bar_full + 8 * pr_s;
                mbar_expect_tx_l0(fb, C::KV_STAGE);
                tma_load_l0(dst, &tm.qkv128, fb, 0, ((3 + 1) * NH + h) * SEQ + pr_st * 128);
                tma_load_l0(dst + 8192, &tm.qkv128, fb, 0, ((3 + 2) * NH + h) * SEQ + pr_st * 128);
            }
            if (pr_st == 0) { if (++pr_qs == 2) { pr_qs = 0; pr_qph ^= 1; } }
            if (++pr_s == KVST) { pr_s = 0; pr_ph ^= 1; }
            if (++pr_st == 16) { pr_st = 0; pr_t += gridDim.x; }
        }
    };
#pragma unroll 1
    for (int i = 0; i < KVST - 1; i++) produce();

    int s = 0, qs = 0;
    uint32_t ph = 0, qph = 0;
    const int qrow = wg * 64 + warp * 16 + (lane & 7) + ((lane >> 3) & 1) * 8;
    constexpr uint32_t DV_STEP = 64u - (64u << 16);
    const uint32_t k_lo0 = desc_lo(sb, 16);
    const uint32_t v_lo0 = desc_lo(sb + 8192, C::OFF_ONES - 8192);
    constexpr uint32_t V_STAGE_STEP = 1024u - (1024u << 16);
    for (int t = blockIdx.x; t < C::NTASK; t += gridDim.x) {
        const int h = t / (SEQ / C::QROWS), qt = t % (SEQ / C::QROWS);
        int fast;
        {
            float qm = 0.f, km = 0.f, vm = 0.f;
#pragma unroll
            for (int i = 0; i < 4; i++) {
                qm = nanmax(qm, g_norm[(0 * NH + h) * 128 + lane + 32 * i]);
                km = nanmax(km, g_norm[(1 * NH + h) * 128 + lane + 32 * i]);
                vm = nanmax(vm, g_norm[(2 * NH + h) * 128 + lane + 32 * i]);
            }
#pragma unroll
            for (int o = 1; o < 32; o <<= 1) {
                qm = nanmax(qm, __shfl_xor_sync(0xffffffffu, qm, o));
                km = nanmax(km, __shfl_xor_sync(0xffffffffu, km, o));
                vm = nanmax(vm, __shfl_xor_sync(0xffffffffu, vm, o));
            }
            const int okf = (qm * km * 1.05f <= SAFE_BOUND * SAFE_BOUND) && (qm < 1e30f) && (km < 1e30f) &&
                            (vm >= 0.0009765625f) && (vm <= 1048576.f);
            fast = __shfl_sync(0xffffffffu, okf, 0);
        }
        uint32_t q[8];
        mbar_wait(bar_qfull + 8 * qs, qph);
        {
            const uint32_t qa = sb + C::OFF_Q + qs * C::QROWS * 64 + qrow * 64;
            const uint32_t x = (qrow >> 1) & 3, c = lane >> 4;
            ldsm_x4(qa + (((0 + c) ^ x) << 4), q[0], q[1], q[2], q[3]);
            ldsm_x4(qa + (((2 + c) ^ x) << 4), q[4], q[5], q[6], q[7]);
        }
        fence_regs_u<8>(q);
        __syncwarp();
        mbar_arrive_lane0(bar_qempty + 8 * qs);
        if (++qs == 2) { qs = 0; qph ^= 1; }

        float o[20];
#pragma unroll
        for (int i = 0; i < 20; i++) o[i] = 0.f;
        fence_regs<20>(o);

        if (fast) {
            float s0[32], s1[32];
            uint32_t p0[16], p1_[16];
            uint32_t* p1 = W1 ? p1_ : p0;
            auto qk = [&](float* sc, uint32_t dK) {
                wg_fence();
                wg_rs64_z(sc, q[0], q[1], q[2], q[3], dK);
                wg_rs64(sc, q[4], q[5], q[6], q[7], dK + 2);
                wg_commit();
            };
            auto exp_pv = [&](const float* sc, uint32_t* p, uint32_t dV) {
#pragma unroll
                for (int kk = 0; kk < 4; kk++) {
                    if (kk & 1) exp_pack8<(MASK16 >> 8) & 0xFF>(sc + 8 * kk, p + 4 * kk);
                    else exp_pack8<MASK16 & 0xFF>(sc + 8 * kk, p + 4 * kk);
                    wg_fence();
                    wg_rs40t(o, p[4 * kk], p[4 * kk + 1], p[4 * kk + 2], p[4 * kk + 3], dV + kk * DV_STEP);
                }
                wg_commit();
            };
            mbar_wait(bar_full + 8 * s, ph);
            qk(s0, k_lo0 + s * 1024);
            wg_wait<0>();
            fence_regs<32>(s0);
            int sprev = s;
#pragma unroll 1
            for (int st = 0; st < 15; st++) {
                const uint32_t dK = k_lo0 + s * 1024, dV = v_lo0 + s * V_STAGE_STEP;
                qk(s1, dK + 256);
                exp_pv(s0, p0, dV);
                if (W1) wg_wait<1>(); else wg_wait<0>();
                fence_regs<32>(s1);
                if (W1) { if (st > 0) mbar_arrive_lane0(bar_empty + 8 * sprev); }
                sprev = s;
                if (++s == KVST) { s = 0; ph ^= 1; }
                mbar_wait(bar_full + 8 * s, ph);
                qk(s0, k_lo0 + s * 1024);
                exp_pv(s1, p1, dV + 4 * DV_STEP);
                if (W1) wg_wait<1>(); else wg_wait<0>();
                fence_regs<32>(s0);
                if (!W1) mbar_arrive_lane0(bar_empty + 8 * sprev);
                produce();
            }
            {
                const uint32_t dK = k_lo0 + s * 1024, dV = v_lo0 + s * V_STAGE_STEP;
                qk(s1, dK + 256);
                exp_pv(s0, p0, dV);
                if (W1) wg_wait<1>(); else wg_wait<0>();
                fence_regs<32>(s1);
                if (W1) mbar_arrive_lane0(bar_empty + 8 * sprev);
                exp_pv(s1, p1, dV + 4 * DV_STEP);
                wg_wait<0>();
                fence_regs<20>(o);
                mbar_arrive_lane0(bar_empty + 8 * s);
                if (++s == KVST) { s = 0; ph ^= 1; }
                produce();
            }
        } else {
            float sc[32];
            uint32_t p[16];
            float m0 = -INFINITY, m1 = -INFINITY;
#pragma unroll 1
            for (int st = 0; st < 16; st++) {
                mbar_wait(bar_full + 8 * s, ph);
                const uint32_t dK = k_lo0 + s * 1024, dV = v_lo0 + s * V_STAGE_STEP;
#pragma unroll 1
                for (int sub = 0; sub < 2; sub++) {
                    wg_fence();
                    wg_rs64_z(sc, q[0], q[1], q[2], q[3], dK + sub * 256);
                    wg_rs64(sc, q[4], q[5], q[6], q[7], dK + sub * 256 + 2);
                    wg_commit();
                    wg_wait<0>();
                    fence_regs<32>(sc);
                    float x0 = m0, x1 = m1;
#pragma unroll
                    for (int j = 0; j < 8; j++) {
                        x0 = fmaxf(x0, fmaxf(sc[4 * j], sc[4 * j + 1]));
                        x1 = fmaxf(x1, fmaxf(sc[4 * j + 2], sc[4 * j + 3]));
                    }
                    x0 = fmaxf(x0, __shfl_xor_sync(0xffffffffu, x0, 1)); x0 = fmaxf(x0, __shfl_xor_sync(0xffffffffu, x0, 2));
                    x1 = fmaxf(x1, __shfl_xor_sync(0xffffffffu, x1, 1)); x1 = fmaxf(x1, __shfl_xor_sync(0xffffffffu, x1, 2));
                    const float al0 = ex2(m0 - x0), al1 = ex2(m1 - x1);
                    m0 = x0; m1 = x1;
#pragma unroll
                    for (int j = 0; j < 5; j++) { o[4 * j] *= al0; o[4 * j + 1] *= al0; o[4 * j + 2] *= al1; o[4 * j + 3] *= al1; }
#pragma unroll
                    for (int j = 0; j < 8; j++) {
                        p[2 * j] = pack_bf16(ex2(sc[4 * j] - x0), ex2(sc[4 * j + 1] - x0));
                        p[2 * j + 1] = pack_bf16(ex2(sc[4 * j + 2] - x1), ex2(sc[4 * j + 3] - x1));
                    }
                    fence_regs<20>(o); fence_regs_u<16>(p);
                    wg_fence();
#pragma unroll
                    for (int kk = 0; kk < 4; kk++) wg_rs40t(o, p[4 * kk], p[4 * kk + 1], p[4 * kk + 2], p[4 * kk + 3], dV + (sub * 4 + kk) * DV_STEP);
                    wg_commit();
                    wg_wait<0>();
                    fence_regs<20>(o);
                }
                mbar_arrive_lane0(bar_empty + 8 * s);
                produce();
                if (++s == KVST) { s = 0; ph ^= 1; }
            }
        }
        const float l0 = __shfl_sync(0xffffffffu, o[16], lane & ~3), l1 = __shfl_sync(0xffffffffu, o[18], lane & ~3);
        const float i0 = 1.0f / l0, i1 = 1.0f / l1;
        const int tok = qt * C::QROWS + wg * 64 + warp * 16 + (lane >> 2);
        uint32_t* dst = reinterpret_cast<uint32_t*>(g_o + (size_t)(SEQ + tok) * DM + h * 32 + (lane & 3) * 2);
#pragma unroll
        for (int j = 0; j < 4; j++) {
            dst[j * 4] = pack_bf16(o[4 * j] * i0, o[4 * j + 1] * i0);
            dst[j * 4 + 8 * (DM / 2)] = pack_bf16(o[4 * j + 2] * i1, o[4 * j + 3] * i1);
        }
        if (threadIdx.x == 0) TS(3, t < (int)gridDim.x ? 1 : (t < 2 * (int)gridDim.x ? 2 : 3));
    }
}

__device__ __forceinline__ void hedgehog_row(const uint4 raw, uint32_t* pos, uint32_t* neg) {
    float x[8];
    const uint32_t w[4] = {raw.x, raw.y, raw.z, raw.w};
#pragma unroll
    for (int i = 0; i < 4; i++) { x[2 * i] = __uint_as_float(w[i] << 16); x[2 * i + 1] = __uint_as_float(w[i] & 0xffff0000u); }
    float mx = x[0], mn = x[0];
#pragma unroll
    for (int i = 1; i < 8; i++) { mx = fmaxf(mx, x[i]); mn = fminf(mn, x[i]); }
    mx = fmaxf(mx, __shfl_xor_sync(0xffffffffu, mx, 1)); mn = fminf(mn, __shfl_xor_sync(0xffffffffu, mn, 1));
    mx = fmaxf(mx, __shfl_xor_sync(0xffffffffu, mx, 2)); mn = fminf(mn, __shfl_xor_sync(0xffffffffu, mn, 2));
    constexpr float L2E = 1.4426950408889634f;
    const float mxs = -mx * L2E, mns = mn * L2E;
    float ep[8], en[8], sp = 0.f, sn = 0.f;
#pragma unroll
    for (int i = 0; i < 8; i++) {
        ep[i] = ex2(fmaf(x[i], L2E, mxs));
        en[i] = ex2(fmaf(x[i], -L2E, mns));
        sp += ep[i]; sn += en[i];
    }
    sp += __shfl_xor_sync(0xffffffffu, sp, 1); sn += __shfl_xor_sync(0xffffffffu, sn, 1);
    sp += __shfl_xor_sync(0xffffffffu, sp, 2); sn += __shfl_xor_sync(0xffffffffu, sn, 2);
    const float ip = 1.0f / sp, in = 1.0f / sn;
#pragma unroll
    for (int i = 0; i < 4; i++) {
        pos[i] = pack_bf16(ep[2 * i] * ip, ep[2 * i + 1] * ip);
        neg[i] = pack_bf16(en[2 * i] * in, en[2 * i + 1] * in);
    }
}

__global__ void __launch_bounds__(128) lin_kv_kernel() {
    __shared__ __align__(1024) uint8_t sm[8192 + 4096 + 1024];
    const uint32_t sphi = smem_u32(sm), sv = sphi + 8192, sones = sv + 4096;
    const int h = blockIdx.x >> 3, ch = blockIdx.x & 7;
    const int warp = threadIdx.x >> 5, lane = threadIdx.x & 31;
    const int r = lane >> 2, c = lane & 3;
    if (threadIdx.x < 64) asm volatile("st.shared.v4.b32 [%0], {%1, %2, %2, %2};" ::"r"(sones + threadIdx.x * 16), "r"(0x00003F80u), "r"(0u) : "memory");
    pdl_launch();
    pdl_wait();
    if (threadIdx.x == 0) TS(1, 0);
    const __nv_bfloat16* gk = g_qkv + (size_t)((0 * 3 + 1) * NH + h) * SEQ * 32;
    const __nv_bfloat16* gv = g_qkv + (size_t)((0 * 3 + 2) * NH + h) * SEQ * 32;
    float acc[20];
#pragma unroll
    for (int i = 0; i < 20; i++) acc[i] = 0.f;
    fence_regs<20>(acc);
    const uint32_t dA = desc_lo(sphi, 16);
    const uint32_t dB = desc_lo(sv, sones - sv);
    const uint32_t DV_STEP = 64u - (64u << 16);
#pragma unroll 1
    for (int mb = 0; mb < 4; mb++) {
        const int tok0 = ch * 256 + mb * 64;
        const int row0 = warp * 16 + r;
        const uint4 k0 = *reinterpret_cast<const uint4*>(gk + (size_t)(tok0 + row0) * 32 + c * 8);
        const uint4 k1 = *reinterpret_cast<const uint4*>(gk + (size_t)(tok0 + row0 + 8) * 32 + c * 8);
        uint4 vv[2];
#pragma unroll
        for (int i = 0; i < 2; i++) {
            const int idx = threadIdx.x + 128 * i;
            vv[i] = *reinterpret_cast<const uint4*>(gv + (size_t)tok0 * 32 + idx * 8);
        }
        uint32_t pos0[4], neg0[4], pos1[4], neg1[4];
        hedgehog_row(k0, pos0, neg0);
        hedgehog_row(k1, pos1, neg1);
        if (mb > 0) __syncthreads();
        {
            const int ra = row0, rb = row0 + 8;
            asm volatile("st.shared.v4.b32 [%0], {%1, %2, %3, %4};" ::"r"(sphi + ra * 128 + ((c ^ (ra & 7)) << 4)), "r"(pos0[0]), "r"(pos0[1]), "r"(pos0[2]), "r"(pos0[3]) : "memory");
            asm volatile("st.shared.v4.b32 [%0], {%1, %2, %3, %4};" ::"r"(sphi + ra * 128 + (((4 + c) ^ (ra & 7)) << 4)), "r"(neg0[0]), "r"(neg0[1]), "r"(neg0[2]), "r"(neg0[3]) : "memory");
            asm volatile("st.shared.v4.b32 [%0], {%1, %2, %3, %4};" ::"r"(sphi + rb * 128 + ((c ^ (rb & 7)) << 4)), "r"(pos1[0]), "r"(pos1[1]), "r"(pos1[2]), "r"(pos1[3]) : "memory");
            asm volatile("st.shared.v4.b32 [%0], {%1, %2, %3, %4};" ::"r"(sphi + rb * 128 + (((4 + c) ^ (rb & 7)) << 4)), "r"(neg1[0]), "r"(neg1[1]), "r"(neg1[2]), "r"(neg1[3]) : "memory");
#pragma unroll
            for (int i = 0; i < 2; i++) {
                const int idx = threadIdx.x + 128 * i, vr = idx >> 2, vc = idx & 3;
                asm volatile("st.shared.v4.b32 [%0], {%1, %2, %3, %4};" ::"r"(sv + vr * 64 + ((vc ^ ((vr >> 1) & 3)) << 4)), "r"(vv[i].x), "r"(vv[i].y), "r"(vv[i].z), "r"(vv[i].w) : "memory");
            }
        }
        fence_async_smem();
        __syncthreads();
        wg_fence();
#pragma unroll
        for (int kk = 0; kk < 4; kk++) wg_ss40tt(acc, dA + kk * 128, dB + kk * DV_STEP);
        wg_commit();
        wg_wait<0>();
        fence_regs<20>(acc);
    }
    if (threadIdx.x == 0) TS(1, 1);
    float* dst = g_kvp + (size_t)(h * 8 + ch) * 2560 + (warp * 16 + r) * 40 + c * 2;
#pragma unroll
    for (int j = 0; j < 5; j++) {
        *reinterpret_cast<float2*>(dst + j * 8) = make_float2(acc[4 * j], acc[4 * j + 1]);
        *reinterpret_cast<float2*>(dst + 8 * 40 + j * 8) = make_float2(acc[4 * j + 2], acc[4 * j + 3]);
    }
}

__global__ void __launch_bounds__(128) lin_out_kernel() {
    __shared__ __align__(1024) uint8_t sm[8192];
    const uint32_t skv = smem_u32(sm);
    const int h = blockIdx.x >> 3, ch = blockIdx.x & 7;
    const int warp = threadIdx.x >> 5, lane = threadIdx.x & 31;
    const int r = lane >> 2, c = lane & 3;
    pdl_launch();
    pdl_wait();
    if (threadIdx.x == 0) TS(2, 0);
    for (int idx = threadIdx.x; idx < 320; idx += 128) {
        const int f = idx / 5, cg = idx % 5;
        float sum[8];
#pragma unroll
        for (int i = 0; i < 8; i++) sum[i] = 0.f;
#pragma unroll
        for (int pp = 0; pp < 8; pp++) {
            const float4* src = reinterpret_cast<const float4*>(g_kvp + (size_t)(h * 8 + pp) * 2560 + f * 40 + cg * 8);
            const float4 a = src[0], b = src[1];
            sum[0] += a.x; sum[1] += a.y; sum[2] += a.z; sum[3] += a.w; sum[4] += b.x; sum[5] += b.y; sum[6] += b.z; sum[7] += b.w;
        }
        const int half = f >> 5, cc = (f >> 3) & 3, i = f & 7;
        const int kp = half * 32 + 16 * (i >> 2) + 8 * ((i >> 1) & 1) + 2 * cc + (i & 1);
        const uint32_t a = skv + (cg == 4 ? 4096 : 0) + kp * 64 + (((cg & 3) ^ ((kp >> 1) & 3)) << 4);
        asm volatile("st.shared.v4.b32 [%0], {%1, %2, %3, %4};" ::"r"(a), "r"(pack_bf16(sum[0], sum[1])), "r"(pack_bf16(sum[2], sum[3])),
                     "r"(pack_bf16(sum[4], sum[5])), "r"(pack_bf16(sum[6], sum[7])) : "memory");
    }
    fence_async_smem();
    __syncthreads();
    const __nv_bfloat16* gq = g_qkv + (size_t)((0 * 3 + 0) * NH + h) * SEQ * 32;
    const uint32_t dB = desc_lo(skv, 4096);
#pragma unroll 1
    for (int mb = 0; mb < 4; mb++) {
        const int tok = ch * 256 + mb * 64 + warp * 16 + r;
        const uint4 q0 = *reinterpret_cast<const uint4*>(gq + (size_t)tok * 32 + c * 8);
        const uint4 q1 = *reinterpret_cast<const uint4*>(gq + (size_t)(tok + 8) * 32 + c * 8);
        uint32_t pos0[4], neg0[4], pos1[4], neg1[4];
        hedgehog_row(q0, pos0, neg0);
        hedgehog_row(q1, pos1, neg1);
        float acc[20];
        fence_regs_u<4>(pos0); fence_regs_u<4>(pos1); fence_regs_u<4>(neg0); fence_regs_u<4>(neg1);
        wg_fence();
        wg_rs40t_z(acc, pos0[0], pos1[0], pos0[1], pos1[1], dB);
        wg_rs40t(acc, pos0[2], pos1[2], pos0[3], pos1[3], dB + 64);
        wg_rs40t(acc, neg0[0], neg1[0], neg0[1], neg1[1], dB + 128);
        wg_rs40t(acc, neg0[2], neg1[2], neg0[3], neg1[3], dB + 192);
        wg_commit();
        wg_wait<0>();
        fence_regs<20>(acc);
        const float d0 = __shfl_sync(0xffffffffu, acc[16], lane & ~3) + 1e-6f, d1 = __shfl_sync(0xffffffffu, acc[18], lane & ~3) + 1e-6f;
        const float i0 = 1.0f / d0, i1 = 1.0f / d1;
        uint32_t* dst = reinterpret_cast<uint32_t*>(g_o + (size_t)tok * DM + h * 32 + c * 2);
#pragma unroll
        for (int j = 0; j < 4; j++) {
            dst[j * 4] = pack_bf16(acc[4 * j] * i0, acc[4 * j + 1] * i0);
            dst[j * 4 + 8 * (DM / 2)] = pack_bf16(acc[4 * j + 2] * i1, acc[4 * j + 3] * i1);
        }
    }
    if (threadIdx.x == 0) TS(2, 1);
}

typedef CUresult (*EncodeFn)(CUtensorMap*, CUtensorMapDataType, cuuint32_t, void*, const cuuint64_t*, const cuuint64_t*,
                             const cuuint32_t*, const cuuint32_t*, CUtensorMapInterleave, CUtensorMapSwizzle,
                             CUtensorMapL2promotion, CUtensorMapFloatOOBfill);

void make_map(EncodeFn enc, CUtensorMap* m, const void* ptr, uint64_t d0, uint64_t d1, uint32_t b0, uint32_t b1, CUtensorMapSwizzle sw) {
    cuuint64_t dims[2] = {d0, d1};
    cuuint64_t strides[1] = {d0 * 2};
    cuuint32_t box[2] = {b0, b1};
    cuuint32_t es[2] = {1, 1};
    enc(m, CU_TENSOR_MAP_DATA_TYPE_BFLOAT16, 2, const_cast<void*>(ptr), dims, strides, box, es, CU_TENSOR_MAP_INTERLEAVE_NONE, sw,
        CU_TENSOR_MAP_L2_PROMOTION_L2_128B, CU_TENSOR_MAP_FLOAT_OOB_FILL_NONE);
}

template <typename... KArgs, typename... Args>
void launch(void (*k)(KArgs...), int grid, int block, int smem, cudaStream_t st, bool pdl, Args... args) {
    cudaLaunchConfig_t cfg = {};
    cfg.gridDim = dim3(grid); cfg.blockDim = dim3(block); cfg.dynamicSmemBytes = smem; cfg.stream = st;
    cudaLaunchAttribute at[1];
    at[0].id = cudaLaunchAttributeProgrammaticStreamSerialization;
    at[0].val.programmaticStreamSerializationAllowed = 1;
    cfg.attrs = at; cfg.numAttrs = pdl ? 1 : 0;
    cudaLaunchKernelEx(&cfg, k, KArgs(args)...);
}

constexpr int K1_MB = 2, K1_ST = 3;
constexpr int K3_BN = 256, K3_ST = 4;
constexpr int K2_NWG = 4, K2_KVST = 4, K2_MASK = 0x1111, K2_W1 = 0;

}

extern "C" void kernel_launch(void* const* d_in, const int* in_sizes, int n_in, void* d_out, int out_size) {
    (void)in_sizes; (void)n_in; (void)out_size;
    static bool init = false;
    static TMaps tm;
    static int nsm = 132;
    static void* cached[8];
    auto k1 = qkv_gemm_kernel<K1_MB, K1_ST, 240, 24>;
    auto k2 = attn_kernel<K2_NWG, K2_KVST, K2_MASK, K2_W1, 1>;
    auto k3 = out_gemm_kernel<K3_BN, K3_ST, 232, 40>;
    bool same = init;
    for (int i = 0; i < 7 && same; i++) same = cached[i] == d_in[i];
    same = same && cached[7] == d_out;
    if (!same) {
        void* fn = nullptr;
        cudaDriverEntryPointQueryResult qr;
        cudaGetDriverEntryPoint("cuTensorMapEncodeTiled", &fn, cudaEnableDefault, &qr);
        EncodeFn enc = (EncodeFn)fn;
        void *pqkv, *po;
        cudaGetSymbolAddress(&pqkv, g_qkv);
        cudaGetSymbolAddress(&po, g_o);
        make_map(enc, &tm.x[0], d_in[0], 1024, 2048, 64, 128 * K1_MB, CU_TENSOR_MAP_SWIZZLE_128B);
        make_map(enc, &tm.x[1], d_in[4], 1024, 2048, 64, 128 * K1_MB, CU_TENSOR_MAP_SWIZZLE_128B);
        make_map(enc, &tm.w[0], d_in[1], 3072, 1024, 64, 64, CU_TENSOR_MAP_SWIZZLE_128B);
        make_map(enc, &tm.w[1], d_in[5], 3072, 1024, 64, 64, CU_TENSOR_MAP_SWIZZLE_128B);
        make_map(enc, &tm.phi, d_in[2], 32, 1024, 32, 64, CU_TENSOR_MAP_SWIZZLE_64B);
        make_map(enc, &tm.qkv64, pqkv, 32, 2 * 3 * NH * SEQ, 32, 64, CU_TENSOR_MAP_SWIZZLE_64B);
        make_map(enc, &tm.qkv128, pqkv, 32, 2 * 3 * NH * SEQ, 32, 128, CU_TENSOR_MAP_SWIZZLE_64B);
        make_map(enc, &tm.o, po, 1024, 2 * SEQ, 64, 128, CU_TENSOR_MAP_SWIZZLE_128B);
        make_map(enc, &tm.wo[0], d_in[3], 1024, 1024, 64, 64, CU_TENSOR_MAP_SWIZZLE_128B);
        make_map(enc, &tm.wo[1], d_in[6], 1024, 1024, 64, 64, CU_TENSOR_MAP_SWIZZLE_128B);
        make_map(enc, &tm.out, d_out, 2048, 2048, 64, 64, CU_TENSOR_MAP_SWIZZLE_128B);
        cudaFuncSetAttribute(k1, cudaFuncAttributeMaxDynamicSharedMemorySize, QkvCfg<K1_MB, K1_ST>::SMEM);
        cudaFuncSetAttribute(k2, cudaFuncAttributeMaxDynamicSharedMemorySize, AttCfg<K2_NWG, K2_KVST>::SMEM);
        cudaFuncSetAttribute(k3, cudaFuncAttributeMaxDynamicSharedMemorySize, OutCfg<K3_BN, K3_ST>::SMEM);
        int dev = 0;
        cudaGetDevice(&dev);
        cudaDeviceGetAttribute(&nsm, cudaDevAttrMultiProcessorCount, dev);
        for (int i = 0; i < 7; i++) cached[i] = d_in[i];
        cached[7] = d_out;
        init = true;
    }
    cudaStream_t st = cudaStreamPerThread;
    const int ntile = 2 * QkvCfg<K1_MB, K1_ST>::TPP;
    launch(k1, ntile < nsm ? ntile : nsm, 384, QkvCfg<K1_MB, K1_ST>::SMEM, st, false, tm, 0, ntile, 1);
    launch(lin_kv_kernel, 256, 128, 0, st, true);
    launch(lin_out_kernel, 256, 128, 0, st, true);
    const int ntask = AttCfg<K2_NWG, K2_KVST>::NTASK;
    launch(k2, ntask < nsm ? ntask : nsm, AttCfg<K2_NWG, K2_KVST>::THREADS, AttCfg<K2_NWG, K2_KVST>::SMEM, st, true, tm);
    launch(k3, 2 * 16 * OutCfg<K3_BN, K3_ST>::NT, 384, OutCfg<K3_BN, K3_ST>::SMEM, st, true, tm, 0);
}
```

```cpp
#include <cuda_runtime.h>
#include <cuda_bf16.h>
#include <cuda.h>
#include <stdint.h>

namespace {

constexpr int SEQ = 2048;
constexpr int DM = 1024;
constexpr int NH = 32;

__device__ __align__(1024) __nv_bfloat16 g_qkv[2 * 3 * NH * SEQ * 32];
__device__ __align__(1024) __nv_bfloat16 g_o[2 * SEQ * DM];
__device__ float g_norm[3 * NH * 128];
__device__ __align__(16) float g_kvp[NH * 8 * 64 * 40];

#define TS(k, e) do {} while (0)
#define TSC(k, e) do {} while (0)

struct TMaps {
    CUtensorMap x[2];
    CUtensorMap w[2];
    CUtensorMap phi;
    CUtensorMap qkv64;
    CUtensorMap qkv128;
    CUtensorMap o;
    CUtensorMap wo[2];
    CUtensorMap out;
};

__device__ __forceinline__ uint32_t smem_u32(const void* p) { return (uint32_t)__cvta_generic_to_shared(p); }
__device__ __forceinline__ void mbar_init(uint32_t bar, uint32_t cnt) {
    asm volatile("mbarrier.init.shared::cta.b64 [%0], %1;" ::"r"(bar), "r"(cnt) : "memory");
}
__device__ __forceinline__ void mbar_expect_tx(uint32_t bar, uint32_t bytes) {
    asm volatile("mbarrier.arrive.expect_tx.shared::cta.b64 _, [%0], %1;" ::"r"(bar), "r"(bytes) : "memory");
}
__device__ __forceinline__ void mbar_arrive(uint32_t bar) {
    asm volatile("mbarrier.arrive.shared::cta.b64 _, [%0];" ::"r"(bar) : "memory");
}
__device__ __forceinline__ void mbar_wait(uint32_t bar, uint32_t parity) {
    asm volatile(
        "{\n"
        ".reg .pred p;\n"
        ".reg .u32 n;\n"
        "mbarrier.try_wait.parity.shared::cta.b64 p, [%0], %1;\n"
        "@p bra DONE;\n"
        "mov.u32 n, 0;\n"
        "LAB_WAIT:\n"
        "mbarrier.try_wait.parity.shared::cta.b64 p, [%0], %1;\n"
        "@p bra DONE;\n"
        "add.u32 n, n, 1;\n"
        "setp.lt.u32 p, n, 4194304;\n"
        "@p bra LAB_WAIT;\n"
        "trap;\n"
        "DONE:\n"
        "}\n" ::"r"(bar), "r"(parity) : "memory");
}
__device__ __forceinline__ void tma_load(uint32_t dst, const CUtensorMap* m, uint32_t bar, int c0, int c1) {
    asm volatile("cp.async.bulk.tensor.2d.shared::cluster.global.mbarrier::complete_tx::bytes [%0], [%1, {%3, %4}], [%2];"
                 ::"r"(dst), "l"(m), "r"(bar), "r"(c0), "r"(c1) : "memory");
}
__device__ __forceinline__ void tma_load_l0(uint32_t dst, const CUtensorMap* m, uint32_t bar, int c0, int c1) {
    asm volatile("{\n.reg .pred p;\nelect.sync _|p, 0xffffffff;\n"
                 "@p cp.async.bulk.tensor.2d.shared::cluster.global.mbarrier::complete_tx::bytes [%0], [%1, {%3, %4}], [%2];\n}"
                 ::"r"(dst), "l"(m), "r"(bar), "r"(c0), "r"(c1) : "memory");
}
__device__ __forceinline__ void mbar_expect_tx_l0(uint32_t bar, uint32_t bytes) {
    asm volatile("{\n.reg .pred p;\nelect.sync _|p, 0xffffffff;\n"
                 "@p mbarrier.arrive.expect_tx.shared::cta.b64 _, [%0], %1;\n}" ::"r"(bar), "r"(bytes) : "memory");
}
__device__ __forceinline__ void tma_store(const CUtensorMap* m, uint32_t src, int c0, int c1) {
    asm volatile("cp.async.bulk.tensor.2d.global.shared::cta.bulk_group [%0, {%2, %3}], [%1];"
                 ::"l"(m), "r"(src), "r"(c0), "r"(c1) : "memory");
}
__device__ __forceinline__ void bulk_commit() { asm volatile("cp.async.bulk.commit_group;" ::: "memory"); }
template <int N> __device__ __forceinline__ void bulk_wait_read() { asm volatile("cp.async.bulk.wait_group.read %0;" ::"n"(N) : "memory"); }
template <int N> __device__ __forceinline__ void bulk_wait() { asm volatile("cp.async.bulk.wait_group %0;" ::"n"(N) : "memory"); }
__device__ __forceinline__ void prefetch_tmap(const CUtensorMap* m) { asm volatile("prefetch.tensormap [%0];" ::"l"(m) : "memory"); }
__device__ __forceinline__ void fence_async_smem() { asm volatile("fence.proxy.async.shared::cta;" ::: "memory"); }
__device__ __forceinline__ void fence_mbar_init() { asm volatile("fence.mbarrier_init.release.cluster;" ::: "memory"); }
__device__ __forceinline__ void bar_sync(int id, int n) { asm volatile("bar.sync %0, %1;" ::"r"(id), "r"(n) : "memory"); }
__device__ __forceinline__ void bar_arrive(int id, int n) { asm volatile("bar.arrive %0, %1;" ::"r"(id), "r"(n) : "memory"); }
__device__ __forceinline__ void pdl_wait() { asm volatile("griddepcontrol.wait;" ::: "memory"); }
__device__ __forceinline__ void pdl_launch() { asm volatile("griddepcontrol.launch_dependents;" ::: "memory"); }
template <int R> __device__ __forceinline__ void reg_inc() { asm volatile("setmaxnreg.inc.sync.aligned.u32 %0;" ::"n"(R)); }
template <int R> __device__ __forceinline__ void reg_dec() { asm volatile("setmaxnreg.dec.sync.aligned.u32 %0;" ::"n"(R)); }

__device__ __forceinline__ void wg_fence() { asm volatile("wgmma.fence.sync.aligned;" ::: "memory"); }
__device__ __forceinline__ void wg_commit() { asm volatile("wgmma.commit_group.sync.aligned;" ::: "memory"); }
template <int N> __device__ __forceinline__ void wg_wait() { asm volatile("wgmma.wait_group.sync.aligned %0;" ::"n"(N) : "memory"); }
template <int N> __device__ __forceinline__ void fence_regs(float* d) {
#pragma unroll
    for (int i = 0; i < N; i++) asm volatile("" : "+f"(d[i])::"memory");
}
template <int N> __device__ __forceinline__ void fence_regs_u(uint32_t* d) {
#pragma unroll
    for (int i = 0; i < N; i++) asm volatile("" : "+r"(d[i])::"memory");
}
__device__ __forceinline__ uint32_t desc_lo(uint32_t addr, uint32_t lbo) { return ((addr & 0x3FFFF) >> 4) | ((lbo >> 4) << 16); }
__device__ __forceinline__ bool elect_one() {
    uint32_t p;
    asm volatile("{\n.reg .pred p;\nelect.sync _|p, 0xffffffff;\nselp.u32 %0, 1, 0, p;\n}" : "=r"(p));
    return p != 0;
}
__device__ __forceinline__ void mbar_arrive_lane0(uint32_t bar) {
    asm volatile("{\n.reg .pred p;\nelect.sync _|p, 0xffffffff;\n@p mbarrier.arrive.shared::cta.b64 _, [%0];\n}" ::"r"(bar) : "memory");
}
__device__ __forceinline__ uint32_t pack_bf16(float lo, float hi) {
    uint32_t r;
    asm("cvt.rn.bf16x2.f32 %0, %1, %2;" : "=r"(r) : "f"(hi), "f"(lo));
    return r;
}
__device__ __forceinline__ void stsm_x4(uint32_t addr, uint32_t r0, uint32_t r1, uint32_t r2, uint32_t r3) {
    asm volatile("stmatrix.sync.aligned.m8n8.x4.shared.b16 [%0], {%1, %2, %3, %4};" ::"r"(addr), "r"(r0), "r"(r1), "r"(r2), "r"(r3) : "memory");
}
__device__ __forceinline__ void ldsm_x4(uint32_t addr, uint32_t& r0, uint32_t& r1, uint32_t& r2, uint32_t& r3) {
    asm volatile("ldmatrix.sync.aligned.m8n8.x4.shared.b16 {%0, %1, %2, %3}, [%4];" : "=r"(r0), "=r"(r1), "=r"(r2), "=r"(r3) : "r"(addr) : "memory");
}
__device__ __forceinline__ float nanmax(float a, float b) {
    float r;
    asm("max.NaN.f32 %0, %1, %2;" : "=f"(r) : "f"(a), "f"(b));
    return r;
}
__device__ __forceinline__ float ex2(float x) {
    float y;
    asm("ex2.approx.ftz.f32 %0, %1;" : "=f"(y) : "f"(x));
    return y;
}
__device__ __forceinline__ float ex2_poly(float x) {
    float t = x + 12582912.f;
    float r = t - 12582912.f;
    float f = x - r;
    float p = fmaf(0.055171772837638855f, f, 0.2426113784313202f);
    p = fmaf(p, f, 0.6932609677314758f);
    p = fmaf(p, f, 0.9999279975891113f);
    return __int_as_float(__float_as_int(p) + (__float_as_int(t) << 23));
}

struct TrueT { static constexpr bool value = true; };
struct FalseT { static constexpr bool value = false; };

__device__ __forceinline__ void wg_ss128_z(float* d, uint32_t da, uint32_t db) {
    asm volatile("{\n.reg .b64 da, db;\nmov.b64 da, {%64, 0x40000040};\nmov.b64 db, {%65, 0x40000040};\n"
        "wgmma.mma_async.sync.aligned.m64n128k16.f32.bf16.bf16 {%0, %1, %2, %3, %4, %5, %6, %7, %8, %9, %10, %11, %12, %13, %14, %15, %16, %17, %18, %19, %20, %21, %22, %23, %24, %25, %26, %27, %28, %29, %30, %31, %32, %33, %34, %35, %36, %37, %38, %39, %40, %41, %42, %43, %44, %45, %46, %47, %48, %49, %50, %51, %52, %53, %54, %55, %56, %57, %58, %59, %60, %61, %62, %63}, da, db, 0, 1, 1, 0, 1;\n}"
        : "=f"(d[0]), "=f"(d[1]), "=f"(d[2]), "=f"(d[3]), "=f"(d[4]), "=f"(d[5]), "=f"(d[6]), "=f"(d[7]), "=f"(d[8]), "=f"(d[9]), "=f"(d[10]), "=f"(d[11]), "=f"(d[12]), "=f"(d[13]), "=f"(d[14]), "=f"(d[15]), "=f"(d[16]), "=f"(d[17]), "=f"(d[18]), "=f"(d[19]), "=f"(d[20]), "=f"(d[21]), "=f"(d[22]), "=f"(d[23]), "=f"(d[24]), "=f"(d[25]), "=f"(d[26]), "=f"(d[27]), "=f"(d[28]), "=f"(d[29]), "=f"(d[30]), "=f"(d[31]), "=f"(d[32]), "=f"(d[33]), "=f"(d[34]), "=f"(d[35]), "=f"(d[36]), "=f"(d[37]), "=f"(d[38]), "=f"(d[39]), "=f"(d[40]), "=f"(d[41]), "=f"(d[42]), "=f"(d[43]), "=f"(d[44]), "=f"(d[45]), "=f"(d[46]), "=f"(d[47]), "=f"(d[48]), "=f"(d[49]), "=f"(d[50]), "=f"(d[51]), "=f"(d[52]), "=f"(d[53]), "=f"(d[54]), "=f"(d[55]), "=f"(d[56]), "=f"(d[57]), "=f"(d[58]), "=f"(d[59]), "=f"(d[60]), "=f"(d[61]), "=f"(d[62]), "=f"(d[63]) : "r"(da), "r"(db));
}
__device__ __forceinline__ void wg_ss128(float* d, uint32_t da, uint32_t db) {
    asm volatile("{\n.reg .b64 da, db;\nmov.b64 da, {%64, 0x40000040};\nmov.b64 db, {%65, 0x40000040};\n"
        "wgmma.mma_async.sync.aligned.m64n128k16.f32.bf16.bf16 {%0, %1, %2, %3, %4, %5, %6, %7, %8, %9, %10, %11, %12, %13, %14, %15, %16, %17, %18, %19, %20, %21, %22, %23, %24, %25, %26, %27, %28, %29, %30, %31, %32, %33, %34, %35, %36, %37, %38, %39, %40, %41, %42, %43, %44, %45, %46, %47, %48, %49, %50, %51, %52, %53, %54, %55, %56, %57, %58, %59, %60, %61, %62, %63}, da, db, 1, 1, 1, 0, 1;\n}"
        : "+f"(d[0]), "+f"(d[1]), "+f"(d[2]), "+f"(d[3]), "+f"(d[4]), "+f"(d[5]), "+f"(d[6]), "+f"(d[7]), "+f"(d[8]), "+f"(d[9]), "+f"(d[10]), "+f"(d[11]), "+f"(d[12]), "+f"(d[13]), "+f"(d[14]), "+f"(d[15]), "+f"(d[16]), "+f"(d[17]), "+f"(d[18]), "+f"(d[19]), "+f"(d[20]), "+f"(d[21]), "+f"(d[22]), "+f"(d[23]), "+f"(d[24]), "+f"(d[25]), "+f"(d[26]), "+f"(d[27]), "+f"(d[28]), "+f"(d[29]), "+f"(d[30]), "+f"(d[31]), "+f"(d[32]), "+f"(d[33]), "+f"(d[34]), "+f"(d[35]), "+f"(d[36]), "+f"(d[37]), "+f"(d[38]), "+f"(d[39]), "+f"(d[40]), "+f"(d[41]), "+f"(d[42]), "+f"(d[43]), "+f"(d[44]), "+f"(d[45]), "+f"(d[46]), "+f"(d[47]), "+f"(d[48]), "+f"(d[49]), "+f"(d[50]), "+f"(d[51]), "+f"(d[52]), "+f"(d[53]), "+f"(d[54]), "+f"(d[55]), "+f"(d[56]), "+f"(d[57]), "+f"(d[58]), "+f"(d[59]), "+f"(d[60]), "+f"(d[61]), "+f"(d[62]), "+f"(d[63]) : "r"(da), "r"(db));
}
__device__ __forceinline__ void wg_ss192_z(float* d, uint32_t da, uint32_t db) {
    asm volatile("{\n.reg .b64 da, db;\nmov.b64 da, {%96, 0x40000040};\nmov.b64 db, {%97, 0x40000040};\n"
        "wgmma.mma_async.sync.aligned.m64n192k16.f32.bf16.bf16 {%0, %1, %2, %3, %4, %5, %6, %7, %8, %9, %10, %11, %12, %13, %14, %15, %16, %17, %18, %19, %20, %21, %22, %23, %24, %25, %26, %27, %28, %29, %30, %31, %32, %33, %34, %35, %36, %37, %38, %39, %40, %41, %42, %43, %44, %45, %46, %47, %48, %49, %50, %51, %52, %53, %54, %55, %56, %57, %58, %59, %60, %61, %62, %63, %64, %65, %66, %67, %68, %69, %70, %71, %72, %73, %74, %75, %76, %77, %78, %79, %80, %81, %82, %83, %84, %85, %86, %87, %88, %89, %90, %91, %92, %93, %94, %95}, da, db, 0, 1, 1, 0, 1;\n}"
        : "=f"(d[0]), "=f"(d[1]), "=f"(d[2]), "=f"(d[3]), "=f"(d[4]), "=f"(d[5]), "=f"(d[6]), "=f"(d[7]), "=f"(d[8]), "=f"(d[9]), "=f"(d[10]), "=f"(d[11]), "=f"(d[12]), "=f"(d[13]), "=f"(d[14]), "=f"(d[15]), "=f"(d[16]), "=f"(d[17]), "=f"(d[18]), "=f"(d[19]), "=f"(d[20]), "=f"(d[21]), "=f"(d[22]), "=f"(d[23]), "=f"(d[24]), "=f"(d[25]), "=f"(d[26]), "=f"(d[27]), "=f"(d[28]), "=f"(d[29]), "=f"(d[30]), "=f"(d[31]), "=f"(d[32]), "=f"(d[33]), "=f"(d[34]), "=f"(d[35]), "=f"(d[36]), "=f"(d[37]), "=f"(d[38]), "=f"(d[39]), "=f"(d[40]), "=f"(d[41]), "=f"(d[42]), "=f"(d[43]), "=f"(d[44]), "=f"(d[45]), "=f"(d[46]), "=f"(d[47]), "=f"(d[48]), "=f"(d[49]), "=f"(d[50]), "=f"(d[51]), "=f"(d[52]), "=f"(d[53]), "=f"(d[54]), "=f"(d[55]), "=f"(d[56]), "=f"(d[57]), "=f"(d[58]), "=f"(d[59]), "=f"(d[60]), "=f"(d[61]), "=f"(d[62]), "=f"(d[63]), "=f"(d[64]), "=f"(d[65]), "=f"(d[66]), "=f"(d[67]), "=f"(d[68]), "=f"(d[69]), "=f"(d[70]), "=f"(d[71]), "=f"(d[72]), "=f"(d[73]), "=f"(d[74]), "=f"(d[75]), "=f"(d[76]), "=f"(d[77]), "=f"(d[78]), "=f"(d[79]), "=f"(d[80]), "=f"(d[81]), "=f"(d[82]), "=f"(d[83]), "=f"(d[84]), "=f"(d[85]), "=f"(d[86]), "=f"(d[87]), "=f"(d[88]), "=f"(d[89]), "=f"(d[90]), "=f"(d[91]), "=f"(d[92]), "=f"(d[93]), "=f"(d[94]), "=f"(d[95]) : "r"(da), "r"(db));
}
__device__ __forceinline__ void wg_ss192(float* d, uint32_t da, uint32_t db) {
    asm volatile("{\n.reg .b64 da, db;\nmov.b64 da, {%96, 0x40000040};\nmov.b64 db, {%97, 0x40000040};\n"
        "wgmma.mma_async.sync.aligned.m64n192k16.f32.bf16.bf16 {%0, %1, %2, %3, %4, %5, %6, %7, %8, %9, %10, %11, %12, %13, %14, %15, %16, %17, %18, %19, %20, %21, %22, %23, %24, %25, %26, %27, %28, %29, %30, %31, %32, %33, %34, %35, %36, %37, %38, %39, %40, %41, %42, %43, %44, %45, %46, %47, %48, %49, %50, %51, %52, %53, %54, %55, %56, %57, %58, %59, %60, %61, %62, %63, %64, %65, %66, %67, %68, %69, %70, %71, %72, %73, %74, %75, %76, %77, %78, %79, %80, %81, %82, %83, %84, %85, %86, %87, %88, %89, %90, %91, %92, %93, %94, %95}, da, db, 1, 1, 1, 0, 1;\n}"
        : "+f"(d[0]), "+f"(d[1]), "+f"(d[2]), "+f"(d[3]), "+f"(d[4]), "+f"(d[5]), "+f"(d[6]), "+f"(d[7]), "+f"(d[8]), "+f"(d[9]), "+f"(d[10]), "+f"(d[11]), "+f"(d[12]), "+f"(d[13]), "+f"(d[14]), "+f"(d[15]), "+f"(d[16]), "+f"(d[17]), "+f"(d[18]), "+f"(d[19]), "+f"(d[20]), "+f"(d[21]), "+f"(d[22]), "+f"(d[23]), "+f"(d[24]), "+f"(d[25]), "+f"(d[26]), "+f"(d[27]), "+f"(d[28]), "+f"(d[29]), "+f"(d[30]), "+f"(d[31]), "+f"(d[32]), "+f"(d[33]), "+f"(d[34]), "+f"(d[35]), "+f"(d[36]), "+f"(d[37]), "+f"(d[38]), "+f"(d[39]), "+f"(d[40]), "+f"(d[41]), "+f"(d[42]), "+f"(d[43]), "+f"(d[44]), "+f"(d[45]), "+f"(d[46]), "+f"(d[47]), "+f"(d[48]), "+f"(d[49]), "+f"(d[50]), "+f"(d[51]), "+f"(d[52]), "+f"(d[53]), "+f"(d[54]), "+f"(d[55]), "+f"(d[56]), "+f"(d[57]), "+f"(d[58]), "+f"(d[59]), "+f"(d[60]), "+f"(d[61]), "+f"(d[62]), "+f"(d[63]), "+f"(d[64]), "+f"(d[65]), "+f"(d[66]), "+f"(d[67]), "+f"(d[68]), "+f"(d[69]), "+f"(d[70]), "+f"(d[71]), "+f"(d[72]), "+f"(d[73]), "+f"(d[74]), "+f"(d[75]), "+f"(d[76]), "+f"(d[77]), "+f"(d[78]), "+f"(d[79]), "+f"(d[80]), "+f"(d[81]), "+f"(d[82]), "+f"(d[83]), "+f"(d[84]), "+f"(d[85]), "+f"(d[86]), "+f"(d[87]), "+f"(d[88]), "+f"(d[89]), "+f"(d[90]), "+f"(d[91]), "+f"(d[92]), "+f"(d[93]), "+f"(d[94]), "+f"(d[95]) : "r"(da), "r"(db));
}
__device__ __forceinline__ void wg_ss256_z(float* d, uint32_t da, uint32_t db) {
    asm volatile("{\n.reg .b64 da, db;\nmov.b64 da, {%128, 0x40000040};\nmov.b64 db, {%129, 0x40000040};\n"
        "wgmma.mma_async.sync.aligned.m64n256k16.f32.bf16.bf16 {%0, %1, %2, %3, %4, %5, %6, %7, %8, %9, %10, %11, %12, %13, %14, %15, %16, %17, %18, %19, %20, %21, %22, %23, %24, %25, %26, %27, %28, %29, %30, %31, %32, %33, %34, %35, %36, %37, %38, %39, %40, %41, %42, %43, %44, %45, %46, %47, %48, %49, %50, %51, %52, %53, %54, %55, %56, %57, %58, %59, %60, %61, %62, %63, %64, %65, %66, %67, %68, %69, %70, %71, %72, %73, %74, %75, %76, %77, %78, %79, %80, %81, %82, %83, %84, %85, %86, %87, %88, %89, %90, %91, %92, %93, %94, %95, %96, %97, %98, %99, %100, %101, %102, %103, %104, %105, %106, %107, %108, %109, %110, %111, %112, %113, %114, %115, %116, %117, %118, %119, %120, %121, %122, %123, %124, %125, %126, %127}, da, db, 0, 1, 1, 0, 1;\n}"
        : "=f"(d[0]), "=f"(d[1]), "=f"(d[2]), "=f"(d[3]), "=f"(d[4]), "=f"(d[5]), "=f"(d[6]), "=f"(d[7]), "=f"(d[8]), "=f"(d[9]), "=f"(d[10]), "=f"(d[11]), "=f"(d[12]), "=f"(d[13]), "=f"(d[14]), "=f"(d[15]), "=f"(d[16]), "=f"(d[17]), "=f"(d[18]), "=f"(d[19]), "=f"(d[20]), "=f"(d[21]), "=f"(d[22]), "=f"(d[23]), "=f"(d[24]), "=f"(d[25]), "=f"(d[26]), "=f"(d[27]), "=f"(d[28]), "=f"(d[29]), "=f"(d[30]), "=f"(d[31]), "=f"(d[32]), "=f"(d[33]), "=f"(d[34]), "=f"(d[35]), "=f"(d[36]), "=f"(d[37]), "=f"(d[38]), "=f"(d[39]), "=f"(d[40]), "=f"(d[41]), "=f"(d[42]), "=f"(d[43]), "=f"(d[44]), "=f"(d[45]), "=f"(d[46]), "=f"(d[47]), "=f"(d[48]), "=f"(d[49]), "=f"(d[50]), "=f"(d[51]), "=f"(d[52]), "=f"(d[53]), "=f"(d[54]), "=f"(d[55]), "=f"(d[56]), "=f"(d[57]), "=f"(d[58]), "=f"(d[59]), "=f"(d[60]), "=f"(d[61]), "=f"(d[62]), "=f"(d[63]), "=f"(d[64]), "=f"(d[65]), "=f"(d[66]), "=f"(d[67]), "=f"(d[68]), "=f"(d[69]), "=f"(d[70]), "=f"(d[71]), "=f"(d[72]), "=f"(d[73]), "=f"(d[74]), "=f"(d[75]), "=f"(d[76]), "=f"(d[77]), "=f"(d[78]), "=f"(d[79]), "=f"(d[80]), "=f"(d[81]), "=f"(d[82]), "=f"(d[83]), "=f"(d[84]), "=f"(d[85]), "=f"(d[86]), "=f"(d[87]), "=f"(d[88]), "=f"(d[89]), "=f"(d[90]), "=f"(d[91]), "=f"(d[92]), "=f"(d[93]), "=f"(d[94]), "=f"(d[95]), "=f"(d[96]), "=f"(d[97]), "=f"(d[98]), "=f"(d[99]), "=f"(d[100]), "=f"(d[101]), "=f"(d[102]), "=f"(d[103]), "=f"(d[104]), "=f"(d[105]), "=f"(d[106]), "=f"(d[107]), "=f"(d[108]), "=f"(d[109]), "=f"(d[110]), "=f"(d[111]), "=f"(d[112]), "=f"(d[113]), "=f"(d[114]), "=f"(d[115]), "=f"(d[116]), "=f"(d[117]), "=f"(d[118]), "=f"(d[119]), "=f"(d[120]), "=f"(d[121]), "=f"(d[122]), "=f"(d[123]), "=f"(d[124]), "=f"(d[125]), "=f"(d[126]), "=f"(d[127]) : "r"(da), "r"(db));
}
__device__ __forceinline__ void wg_ss256(float* d, uint32_t da, uint32_t db) {
    asm volatile("{\n.reg .b64 da, db;\nmov.b64 da, {%128, 0x40000040};\nmov.b64 db, {%129, 0x40000040};\n"
        "wgmma.mma_async.sync.aligned.m64n256k16.f32.bf16.bf16 {%0, %1, %2, %3, %4, %5, %6, %7, %8, %9, %10, %11, %12, %13, %14, %15, %16, %17, %18, %19, %20, %21, %22, %23, %24, %25, %26, %27, %28, %29, %30, %31, %32, %33, %34, %35, %36, %37, %38, %39, %40, %41, %42, %43, %44, %45, %46, %47, %48, %49, %50, %51, %52, %53, %54, %55, %56, %57, %58, %59, %60, %61, %62, %63, %64, %65, %66, %67, %68, %69, %70, %71, %72, %73, %74, %75, %76, %77, %78, %79, %80, %81, %82, %83, %84, %85, %86, %87, %88, %89, %90, %91, %92, %93, %94, %95, %96, %97, %98, %99, %100, %101, %102, %103, %104, %105, %106, %107, %108, %109, %110, %111, %112, %113, %114, %115, %116, %117, %118, %119, %120, %121, %122, %123, %124, %125, %126, %127}, da, db, 1, 1, 1, 0, 1;\n}"
        : "+f"(d[0]), "+f"(d[1]), "+f"(d[2]), "+f"(d[3]), "+f"(d[4]), "+f"(d[5]), "+f"(d[6]), "+f"(d[7]), "+f"(d[8]), "+f"(d[9]), "+f"(d[10]), "+f"(d[11]), "+f"(d[12]), "+f"(d[13]), "+f"(d[14]), "+f"(d[15]), "+f"(d[16]), "+f"(d[17]), "+f"(d[18]), "+f"(d[19]), "+f"(d[20]), "+f"(d[21]), "+f"(d[22]), "+f"(d[23]), "+f"(d[24]), "+f"(d[25]), "+f"(d[26]), "+f"(d[27]), "+f"(d[28]), "+f"(d[29]), "+f"(d[30]), "+f"(d[31]), "+f"(d[32]), "+f"(d[33]), "+f"(d[34]), "+f"(d[35]), "+f"(d[36]), "+f"(d[37]), "+f"(d[38]), "+f"(d[39]), "+f"(d[40]), "+f"(d[41]), "+f"(d[42]), "+f"(d[43]), "+f"(d[44]), "+f"(d[45]), "+f"(d[46]), "+f"(d[47]), "+f"(d[48]), "+f"(d[49]), "+f"(d[50]), "+f"(d[51]), "+f"(d[52]), "+f"(d[53]), "+f"(d[54]), "+f"(d[55]), "+f"(d[56]), "+f"(d[57]), "+f"(d[58]), "+f"(d[59]), "+f"(d[60]), "+f"(d[61]), "+f"(d[62]), "+f"(d[63]), "+f"(d[64]), "+f"(d[65]), "+f"(d[66]), "+f"(d[67]), "+f"(d[68]), "+f"(d[69]), "+f"(d[70]), "+f"(d[71]), "+f"(d[72]), "+f"(d[73]), "+f"(d[74]), "+f"(d[75]), "+f"(d[76]), "+f"(d[77]), "+f"(d[78]), "+f"(d[79]), "+f"(d[80]), "+f"(d[81]), "+f"(d[82]), "+f"(d[83]), "+f"(d[84]), "+f"(d[85]), "+f"(d[86]), "+f"(d[87]), "+f"(d[88]), "+f"(d[89]), "+f"(d[90]), "+f"(d[91]), "+f"(d[92]), "+f"(d[93]), "+f"(d[94]), "+f"(d[95]), "+f"(d[96]), "+f"(d[97]), "+f"(d[98]), "+f"(d[99]), "+f"(d[100]), "+f"(d[101]), "+f"(d[102]), "+f"(d[103]), "+f"(d[104]), "+f"(d[105]), "+f"(d[106]), "+f"(d[107]), "+f"(d[108]), "+f"(d[109]), "+f"(d[110]), "+f"(d[111]), "+f"(d[112]), "+f"(d[113]), "+f"(d[114]), "+f"(d[115]), "+f"(d[116]), "+f"(d[117]), "+f"(d[118]), "+f"(d[119]), "+f"(d[120]), "+f"(d[121]), "+f"(d[122]), "+f"(d[123]), "+f"(d[124]), "+f"(d[125]), "+f"(d[126]), "+f"(d[127]) : "r"(da), "r"(db));
}
__device__ __forceinline__ void wg_rs64_z(float* d, uint32_t a0, uint32_t a1, uint32_t a2, uint32_t a3, uint32_t db) {
    asm volatile("{\n.reg .b64 db;\nmov.b64 db, {%36, 0x80000020};\n"
        "wgmma.mma_async.sync.aligned.m64n64k16.f32.bf16.bf16 {%0, %1, %2, %3, %4, %5, %6, %7, %8, %9, %10, %11, %12, %13, %14, %15, %16, %17, %18, %19, %20, %21, %22, %23, %24, %25, %26, %27, %28, %29, %30, %31}, {%32, %33, %34, %35}, db, 0, 1, 1, 0;\n}"
        : "=f"(d[0]), "=f"(d[1]), "=f"(d[2]), "=f"(d[3]), "=f"(d[4]), "=f"(d[5]), "=f"(d[6]), "=f"(d[7]), "=f"(d[8]), "=f"(d[9]), "=f"(d[10]), "=f"(d[11]), "=f"(d[12]), "=f"(d[13]), "=f"(d[14]), "=f"(d[15]), "=f"(d[16]), "=f"(d[17]), "=f"(d[18]), "=f"(d[19]), "=f"(d[20]), "=f"(d[21]), "=f"(d[22]), "=f"(d[23]), "=f"(d[24]), "=f"(d[25]), "=f"(d[26]), "=f"(d[27]), "=f"(d[28]), "=f"(d[29]), "=f"(d[30]), "=f"(d[31]) : "r"(a0), "r"(a1), "r"(a2), "r"(a3), "r"(db));
}
__device__ __forceinline__ void wg_rs64(float* d, uint32_t a0, uint32_t a1, uint32_t a2, uint32_t a3, uint32_t db) {
    asm volatile("{\n.reg .b64 db;\nmov.b64 db, {%36, 0x80000020};\n"
        "wgmma.mma_async.sync.aligned.m64n64k16.f32.bf16.bf16 {%0, %1, %2, %3, %4, %5, %6, %7, %8, %9, %10, %11, %12, %13, %14, %15, %16, %17, %18, %19, %20, %21, %22, %23, %24, %25, %26, %27, %28, %29, %30, %31}, {%32, %33, %34, %35}, db, 1, 1, 1, 0;\n}"
        : "+f"(d[0]), "+f"(d[1]), "+f"(d[2]), "+f"(d[3]), "+f"(d[4]), "+f"(d[5]), "+f"(d[6]), "+f"(d[7]), "+f"(d[8]), "+f"(d[9]), "+f"(d[10]), "+f"(d[11]), "+f"(d[12]), "+f"(d[13]), "+f"(d[14]), "+f"(d[15]), "+f"(d[16]), "+f"(d[17]), "+f"(d[18]), "+f"(d[19]), "+f"(d[20]), "+f"(d[21]), "+f"(d[22]), "+f"(d[23]), "+f"(d[24]), "+f"(d[25]), "+f"(d[26]), "+f"(d[27]), "+f"(d[28]), "+f"(d[29]), "+f"(d[30]), "+f"(d[31]) : "r"(a0), "r"(a1), "r"(a2), "r"(a3), "r"(db));
}
__device__ __forceinline__ void wg_rs40t(float* d, uint32_t a0, uint32_t a1, uint32_t a2, uint32_t a3, uint32_t db) {
    asm volatile("{\n.reg .b64 db;\nmov.b64 db, {%24, 0x80000020};\n"
        "wgmma.mma_async.sync.aligned.m64n40k16.f32.bf16.bf16 {%0, %1, %2, %3, %4, %5, %6, %7, %8, %9, %10, %11, %12, %13, %14, %15, %16, %17, %18, %19}, {%20, %21, %22, %23}, db, 1, 1, 1, 1;\n}"
        : "+f"(d[0]), "+f"(d[1]), "+f"(d[2]), "+f"(d[3]), "+f"(d[4]), "+f"(d[5]), "+f"(d[6]), "+f"(d[7]), "+f"(d[8]), "+f"(d[9]), "+f"(d[10]), "+f"(d[11]), "+f"(d[12]), "+f"(d[13]), "+f"(d[14]), "+f"(d[15]), "+f"(d[16]), "+f"(d[17]), "+f"(d[18]), "+f"(d[19]) : "r"(a0), "r"(a1), "r"(a2), "r"(a3), "r"(db));
}
__device__ __forceinline__ void wg_rs40t_z(float* d, uint32_t a0, uint32_t a1, uint32_t a2, uint32_t a3, uint32_t db) {
    asm volatile("{\n.reg .b64 db;\nmov.b64 db, {%24, 0x80000020};\n"
        "wgmma.mma_async.sync.aligned.m64n40k16.f32.bf16.bf16 {%0, %1, %2, %3, %4, %5, %6, %7, %8, %9, %10, %11, %12, %13, %14, %15, %16, %17, %18, %19}, {%20, %21, %22, %23}, db, 0, 1, 1, 1;\n}"
        : "=f"(d[0]), "=f"(d[1]), "=f"(d[2]), "=f"(d[3]), "=f"(d[4]), "=f"(d[5]), "=f"(d[6]), "=f"(d[7]), "=f"(d[8]), "=f"(d[9]), "=f"(d[10]), "=f"(d[11]), "=f"(d[12]), "=f"(d[13]), "=f"(d[14]), "=f"(d[15]), "=f"(d[16]), "=f"(d[17]), "=f"(d[18]), "=f"(d[19]) : "r"(a0), "r"(a1), "r"(a2), "r"(a3), "r"(db));
}
__device__ __forceinline__ void wg_rs32t_z(float* d, uint32_t a0, uint32_t a1, uint32_t a2, uint32_t a3, uint32_t db) {
    asm volatile("{\n.reg .b64 db;\nmov.b64 db, {%20, 0x80000020};\n"
        "wgmma.mma_async.sync.aligned.m64n32k16.f32.bf16.bf16 {%0, %1, %2, %3, %4, %5, %6, %7, %8, %9, %10, %11, %12, %13, %14, %15}, {%16, %17, %18, %19}, db, 0, 1, 1, 1;\n}"
        : "=f"(d[0]), "=f"(d[1]), "=f"(d[2]), "=f"(d[3]), "=f"(d[4]), "=f"(d[5]), "=f"(d[6]), "=f"(d[7]), "=f"(d[8]), "=f"(d[9]), "=f"(d[10]), "=f"(d[11]), "=f"(d[12]), "=f"(d[13]), "=f"(d[14]), "=f"(d[15]) : "r"(a0), "r"(a1), "r"(a2), "r"(a3), "r"(db));
}
__device__ __forceinline__ void wg_rs32t(float* d, uint32_t a0, uint32_t a1, uint32_t a2, uint32_t a3, uint32_t db) {
    asm volatile("{\n.reg .b64 db;\nmov.b64 db, {%20, 0x80000020};\n"
        "wgmma.mma_async.sync.aligned.m64n32k16.f32.bf16.bf16 {%0, %1, %2, %3, %4, %5, %6, %7, %8, %9, %10, %11, %12, %13, %14, %15}, {%16, %17, %18, %19}, db, 1, 1, 1, 1;\n}"
        : "+f"(d[0]), "+f"(d[1]), "+f"(d[2]), "+f"(d[3]), "+f"(d[4]), "+f"(d[5]), "+f"(d[6]), "+f"(d[7]), "+f"(d[8]), "+f"(d[9]), "+f"(d[10]), "+f"(d[11]), "+f"(d[12]), "+f"(d[13]), "+f"(d[14]), "+f"(d[15]) : "r"(a0), "r"(a1), "r"(a2), "r"(a3), "r"(db));
}
__device__ __forceinline__ void wg_ss40tt(float* d, uint32_t da, uint32_t db) {
    asm volatile("{\n.reg .b64 da, db;\nmov.b64 da, {%20, 0x40000040};\nmov.b64 db, {%21, 0x80000020};\n"
        "wgmma.mma_async.sync.aligned.m64n40k16.f32.bf16.bf16 {%0, %1, %2, %3, %4, %5, %6, %7, %8, %9, %10, %11, %12, %13, %14, %15, %16, %17, %18, %19}, da, db, 1, 1, 1, 1, 1;\n}"
        : "+f"(d[0]), "+f"(d[1]), "+f"(d[2]), "+f"(d[3]), "+f"(d[4]), "+f"(d[5]), "+f"(d[6]), "+f"(d[7]), "+f"(d[8]), "+f"(d[9]), "+f"(d[10]), "+f"(d[11]), "+f"(d[12]), "+f"(d[13]), "+f"(d[14]), "+f"(d[15]), "+f"(d[16]), "+f"(d[17]), "+f"(d[18]), "+f"(d[19]) : "r"(da), "r"(db));
}

constexpr float QSCALE = 0.17677669529663687f * 1.4426950408889634f;

template <int MB, int STAGES> struct QkvCfg {
    static constexpr int BM = 128 * MB;
    static constexpr int A_BYTES = BM * 128;
    static constexpr int B_BYTES = 3 * 8192;
    static constexpr int STAGE = A_BYTES + B_BYTES;
    static constexpr int OFF_STG = STAGES * STAGE;
    static constexpr int OFF_PHI = OFF_STG + 2 * 24576;
    static constexpr int OFF_BAR = OFF_PHI + 4096;
    static constexpr int SMEM = OFF_BAR + 128 + 1024;
    static constexpr int MT = SEQ / BM;
    static constexpr int TPP = MT * 16;
};

template <int MB, int STAGES, int RC, int RP>
__global__ void __launch_bounds__(384, 1)
qkv_gemm_kernel(const __grid_constant__ TMaps tm, int tile_begin, int tile_end, int first_prob) {
    using C = QkvCfg<MB, STAGES>;
    extern __shared__ uint8_t smem_raw[];
    const uint32_t sb = (smem_u32(smem_raw) + 1023) & ~1023u;
    const uint32_t bar_full = sb + C::OFF_BAR, bar_empty = bar_full + 8 * STAGES;
    const uint32_t bar_phi_full = bar_empty + 8 * STAGES, bar_phi_empty = bar_phi_full + 8;
    const int wg = __shfl_sync(0xffffffffu, threadIdx.x >> 7, 0);
    const int warp = __shfl_sync(0xffffffffu, (threadIdx.x >> 5) & 3, 0), lane = threadIdx.x & 31;

    if (threadIdx.x == 0) {
        for (int s = 0; s < STAGES; s++) { mbar_init(bar_full + 8 * s, 1); mbar_init(bar_empty + 8 * s, 8); }
        mbar_init(bar_phi_full, 1);
        mbar_init(bar_phi_empty, 8);
        fence_mbar_init();
    }
    __syncthreads();
    pdl_launch();
    if (threadIdx.x == 0) { TS(0, 0); TSC(5, 0); }

    if (wg == 2) {
        reg_dec<RP>();
        if (warp == 0 && lane == 0) {
            prefetch_tmap(&tm.x[0]); prefetch_tmap(&tm.x[1]); prefetch_tmap(&tm.w[0]); prefetch_tmap(&tm.w[1]);
            int s = 0; uint32_t ph = 1; uint32_t phi_ph = 1;
            for (int t = tile_begin + blockIdx.x; t < tile_end; t += gridDim.x) {
                const int pi = t / C::TPP, tt = t % C::TPP;
                const int prob = pi == 0 ? first_prob : 1 - first_prob;
                const int mt = tt % C::MT, nt = tt / C::MT;
                const CUtensorMap* mx = &tm.x[prob];
                const CUtensorMap* mw = &tm.w[prob];
                for (int kt = 0; kt < 16; kt++) {
                    mbar_wait(bar_empty + 8 * s, ph);
                    const uint32_t st = sb + s * C::STAGE, fb = bar_full + 8 * s;
                    mbar_expect_tx(fb, C::STAGE);
                    tma_load(st, mx, fb, kt * 64, mt * C::BM);
#pragma unroll
                    for (int p = 0; p < 3; p++) tma_load(st + C::A_BYTES + p * 8192, mw, fb, p * 1024 + nt * 64, kt * 64);
                    if (++s == STAGES) { s = 0; ph ^= 1; }
                    if (kt == 2 && prob == 0) {
                        mbar_wait(bar_phi_empty, phi_ph);
                        mbar_expect_tx(bar_phi_full, 4096);
                        tma_load(sb + C::OFF_PHI, &tm.phi, bar_phi_full, 0, nt * 64);
                        phi_ph ^= 1;
                    }
                }
            }
        }
    } else {
        reg_inc<RC>();
        float acc[MB][96];
        int s = 0; uint32_t ph = 0; uint32_t phi_ph = 0;
        for (int t = tile_begin + blockIdx.x; t < tile_end; t += gridDim.x) {
            const int pi = t / C::TPP, tt = t % C::TPP;
            const int prob = pi == 0 ? first_prob : 1 - first_prob;
            const int mt = tt % C::MT, nt = tt / C::MT;
            int prev = 0;
            auto kstep = [&](auto first) {
                mbar_wait(bar_full + 8 * s, ph);
                const uint32_t st = sb + s * C::STAGE;
                const uint32_t dA = desc_lo(st + wg * (64 * MB * 128), 16);
                const uint32_t dB = desc_lo(st + C::A_BYTES, 8192);
                wg_fence();
#pragma unroll
                for (int kk = 0; kk < 4; kk++) {
#pragma unroll
                    for (int mb = 0; mb < MB; mb++) {
                        if (decltype(first)::value && kk == 0) wg_ss192_z(acc[mb], dA + mb * 512 + kk * 2, dB + kk * 128);
                        else wg_ss192(acc[mb], dA + mb * 512 + kk * 2, dB + kk * 128);
                    }
                }
                wg_commit();
                if (!decltype(first)::value) {
                    wg_wait<1>();
                    mbar_arrive_lane0(bar_empty + 8 * prev);
                }
                prev = s;
                if (++s == STAGES) { s = 0; ph ^= 1; }
            };
            kstep(TrueT{});
            if (threadIdx.x == 0) TS(0, t < (int)gridDim.x ? 1 : 4);
#pragma unroll 1
            for (int kt = 1; kt < 16; kt++) kstep(FalseT{});
            wg_wait<0>();
            if (threadIdx.x == 0) TS(0, t < (int)gridDim.x ? 2 : 5);
            mbar_arrive_lane0(bar_empty + 8 * prev);
#pragma unroll
            for (int mb = 0; mb < MB; mb++) fence_regs<96>(acc[mb]);

            uint32_t tidl;
            asm volatile("mov.u32 %0, %%tid.x;" : "=r"(tidl));
            const int lane = tidl & 31;
            const uint32_t stg = sb + C::OFF_STG + (tidl >> 5) * 6144;
            const int strow = (lane & 7) + ((lane >> 3) & 1) * 8;
            const uint32_t st_base = stg + strow * 64;
            const uint32_t st_x = (strow >> 1) & 3, st_c = lane >> 4;
            const uint32_t ld_base = stg + (lane >> 2) * 64 + (((lane & 3) ^ ((lane >> 3) & 3)) << 4);
            if (prob == 0) { mbar_wait(bar_phi_full, phi_ph); phi_ph ^= 1; }
            float nrm[6];
#pragma unroll
            for (int i = 0; i < 6; i++) nrm[i] = 0.f;
#pragma unroll
            for (int mb = 0; mb < MB; mb++) {
                const int tok0 = mt * C::BM + wg * (64 * MB) + mb * 64 + warp * 16;
                float* a = acc[mb];
                auto stage_block = [&](int sbk, const uint32_t* pk) {
                    stsm_x4(st_base + sbk * 1024 + ((st_c ^ st_x) << 4), pk[0], pk[1], pk[2], pk[3]);
                    stsm_x4(st_base + sbk * 1024 + (((2 + st_c) ^ st_x) << 4), pk[4], pk[5], pk[6], pk[7]);
                };
                if (mb > 0) __syncwarp();
                if (prob == 1) {
#pragma unroll
                    for (int p = 0; p < 3; p++) {
#pragma unroll
                        for (int hh = 0; hh < 2; hh++) {
                            float s0 = 0.f, s1 = 0.f;
                            uint32_t pk[8];
#pragma unroll
                            for (int g = 0; g < 4; g++) {
                                const int j = p * 8 + hh * 4 + g;
                                float v0 = a[4 * j], v1 = a[4 * j + 1], v2 = a[4 * j + 2], v3 = a[4 * j + 3];
                                if (p == 0) { v0 *= QSCALE; v1 *= QSCALE; v2 *= QSCALE; v3 *= QSCALE; }
                                if (p < 2) {
                                    s0 = fmaf(v0, v0, s0); s0 = fmaf(v1, v1, s0);
                                    s1 = fmaf(v2, v2, s1); s1 = fmaf(v3, v3, s1);
                                } else {
                                    s0 = nanmax(s0, nanmax(fabsf(v0), fabsf(v1)));
                                    s1 = nanmax(s1, nanmax(fabsf(v2), fabsf(v3)));
                                }
                                pk[2 * g] = pack_bf16(v0, v1); pk[2 * g + 1] = pack_bf16(v2, v3);
                            }
                            nrm[p * 2 + hh] = nanmax(nrm[p * 2 + hh], nanmax(s0, s1));
                            stage_block(p * 2 + hh, pk);
                        }
                    }
                } else {
#pragma unroll
                    for (int hh = 0; hh < 2; hh++) {
                        uint32_t pk[8];
#pragma unroll
                        for (int g = 0; g < 4; g++) {
                            const int j = 16 + hh * 4 + g;
                            pk[2 * g] = pack_bf16(a[4 * j], a[4 * j + 1]); pk[2 * g + 1] = pack_bf16(a[4 * j + 2], a[4 * j + 3]);
                        }
                        stage_block(4 + hh, pk);
                    }
#pragma unroll
                    for (int p = 0; p < 2; p++) {
                        uint32_t fr[16];
                        float f[2][16];
#pragma unroll
                        for (int j = 0; j < 8; j++) {
                            const int jj = p * 8 + j;
                            fr[2 * j] = pack_bf16(a[4 * jj], a[4 * jj + 1]); fr[2 * j + 1] = pack_bf16(a[4 * jj + 2], a[4 * jj + 3]);
                        }
                        fence_regs_u<16>(fr);
                        wg_fence();
#pragma unroll
                        for (int hh = 0; hh < 2; hh++) {
                            const uint32_t dP = desc_lo(sb + C::OFF_PHI + hh * 2048, 16);
                            wg_rs32t_z(f[hh], fr[8 * hh], fr[8 * hh + 1], fr[8 * hh + 2], fr[8 * hh + 3], dP);
                            wg_rs32t(f[hh], fr[8 * hh + 4], fr[8 * hh + 5], fr[8 * hh + 6], fr[8 * hh + 7], dP + 64);
                        }
                        wg_commit();
                        wg_wait<0>();
                        fence_regs<16>(f[0]); fence_regs<16>(f[1]);
#pragma unroll
                        for (int hh = 0; hh < 2; hh++) {
                            uint32_t pk[8];
#pragma unroll
                            for (int g = 0; g < 4; g++) {
                                pk[2 * g] = pack_bf16(f[hh][4 * g], f[hh][4 * g + 1]); pk[2 * g + 1] = pack_bf16(f[hh][4 * g + 2], f[hh][4 * g + 3]);
                            }
                            stage_block(p * 2 + hh, pk);
                        }
                    }
                    if (mb == MB - 1) mbar_arrive_lane0(bar_phi_empty);
                }
                __syncwarp();
#pragma unroll
                for (int sbk = 0; sbk < 6; sbk++) {
                    const int p = sbk >> 1, hh = sbk & 1;
                    uint4* dst = reinterpret_cast<uint4*>(g_qkv + ((size_t)((prob * 3 + p) * NH + nt * 2 + hh) * SEQ + tok0) * 32) + lane;
#pragma unroll
                    for (int i = 0; i < 2; i++) {
                        uint4 v;
                        asm volatile("ld.shared.v4.b32 {%0, %1, %2, %3}, [%4];" : "=r"(v.x), "=r"(v.y), "=r"(v.z), "=r"(v.w) : "r"(ld_base + sbk * 1024 + i * 512) : "memory");
                        dst[i * 32] = v;
                    }
                }
            }
            if (prob == 1) {
#pragma unroll
                for (int o = 4; o < 32; o <<= 1) {
#pragma unroll
                    for (int i = 0; i < 6; i++) nrm[i] = nanmax(nrm[i], __shfl_xor_sync(0xffffffffu, nrm[i], o));
                }
#pragma unroll
                for (int o = 1; o < 4; o <<= 1) {
#pragma unroll
                    for (int i = 0; i < 6; i++) {
                        const float other = __shfl_xor_sync(0xffffffffu, nrm[i], o);
                        nrm[i] = i < 4 ? nrm[i] + other : nanmax(nrm[i], other);
                    }
                }
                if (lane < 6 * MB) {
                    const int i = lane / MB, sl = lane % MB;
                    float v = nrm[0];
#pragma unroll
                    for (int q = 1; q < 6; q++) v = i == q ? nrm[q] : v;
                    g_norm[((i >> 1) * NH + nt * 2 + (i & 1)) * 128 + (mt * 8 + wg * 4 + warp) * MB + sl] = v;
                }
            }
            if (threadIdx.x == 0) TS(0, t < (int)gridDim.x ? 3 : 6);
        }
        if (threadIdx.x == 0) { TS(0, 7); TSC(5, 1); }
    }
}

template <int BN, int STAGES> struct OutCfg {
    static constexpr int A_BYTES = 128 * 128;
    static constexpr int B_BYTES = (BN / 64) * 8192;
    static constexpr int STAGE = A_BYTES + B_BYTES;
    static constexpr int OFF_BAR = STAGES * STAGE;
    static constexpr int SMEM = OFF_BAR + 128 + 1024;
    static constexpr int NT = DM / BN;
};

template <int BN> __device__ __forceinline__ void wg_ss_z(float* d, uint32_t a, uint32_t b);
template <> __device__ __forceinline__ void wg_ss_z<128>(float* d, uint32_t a, uint32_t b) { wg_ss128_z(d, a, b); }
template <> __device__ __forceinline__ void wg_ss_z<256>(float* d, uint32_t a, uint32_t b) { wg_ss256_z(d, a, b); }
template <int BN> __device__ __forceinline__ void wg_ss(float* d, uint32_t a, uint32_t b);
template <> __device__ __forceinline__ void wg_ss<128>(float* d, uint32_t a, uint32_t b) { wg_ss128(d, a, b); }
template <> __device__ __forceinline__ void wg_ss<256>(float* d, uint32_t a, uint32_t b) { wg_ss256(d, a, b); }

template <int BN, int STAGES, int RC, int RP>
__global__ void __launch_bounds__(384, 1)
out_gemm_kernel(const __grid_constant__ TMaps tm, int prob_begin) {
    using C = OutCfg<BN, STAGES>;
    extern __shared__ uint8_t smem_raw[];
    const uint32_t sb = (smem_u32(smem_raw) + 1023) & ~1023u;
    const uint32_t bar_full = sb + C::OFF_BAR, bar_empty = bar_full + 8 * STAGES;
    const int wg = __shfl_sync(0xffffffffu, threadIdx.x >> 7, 0);
    const int warp = __shfl_sync(0xffffffffu, (threadIdx.x >> 5) & 3, 0), lane = threadIdx.x & 31;
    const int t = blockIdx.x;
    const int prob = prob_begin + t / (16 * C::NT);
    const int mt = (t % (16 * C::NT)) % 16, nt = (t % (16 * C::NT)) / 16;

    if (threadIdx.x == 0) {
        for (int s = 0; s < STAGES; s++) { mbar_init(bar_full + 8 * s, 1); mbar_init(bar_empty + 8 * s, 8); }
        fence_mbar_init();
    }
    __syncthreads();

    if (threadIdx.x == 0) TS(4, 0);
    if (wg == 2) {
        reg_dec<RP>();
        if (warp == 0 && lane == 0) {
            const CUtensorMap* mw = &tm.wo[prob];
            prefetch_tmap(mw); prefetch_tmap(&tm.o); prefetch_tmap(&tm.out);
#pragma unroll
            for (int s = 0; s < STAGES; s++) {
                const uint32_t st = sb + s * C::STAGE, fb = bar_full + 8 * s;
                mbar_expect_tx(fb, C::STAGE);
#pragma unroll
                for (int p = 0; p < BN / 64; p++) tma_load(st + C::A_BYTES + p * 8192, mw, fb, nt * BN + p * 64, s * 64);
            }
            pdl_wait();
            TS(4, 1);
#pragma unroll
            for (int s = 0; s < STAGES; s++) tma_load(sb + s * C::STAGE, &tm.o, bar_full + 8 * s, s * 64, prob * SEQ + mt * 128);
            int s = 0; uint32_t ph = 0;
            for (int kt = STAGES; kt < 16; kt++) {
                mbar_wait(bar_empty + 8 * s, ph);
                const uint32_t st = sb + s * C::STAGE, fb = bar_full + 8 * s;
                mbar_expect_tx(fb, C::STAGE);
                tma_load(st, &tm.o, fb, kt * 64, prob * SEQ + mt * 128);
#pragma unroll
                for (int p = 0; p < BN / 64; p++) tma_load(st + C::A_BYTES + p * 8192, mw, fb, nt * BN + p * 64, kt * 64);
                if (++s == STAGES) { s = 0; ph ^= 1; }
            }
        }
    } else {
        reg_inc<RC>();
        float acc[BN / 2];
        int s = 0; uint32_t ph = 0; int prev = 0;
        auto kstep = [&](auto first) {
            mbar_wait(bar_full + 8 * s, ph);
            const uint32_t st = sb + s * C::STAGE;
            const uint32_t dA = desc_lo(st + wg * (64 * 128), 16);
            const uint32_t dB = desc_lo(st + C::A_BYTES, 8192);
            wg_fence();
#pragma unroll
            for (int kk = 0; kk < 4; kk++) {
                if (decltype(first)::value && kk == 0) wg_ss_z<BN>(acc, dA + kk * 2, dB + kk * 128);
                else wg_ss<BN>(acc, dA + kk * 2, dB + kk * 128);
            }
            wg_commit();
            if (!decltype(first)::value) {
                wg_wait<1>();
                mbar_arrive_lane0(bar_empty + 8 * prev);
            }
            prev = s;
            if (++s == STAGES) { s = 0; ph ^= 1; }
        };
        kstep(TrueT{});
        if (threadIdx.x == 0) TS(4, 2);
#pragma unroll 1
        for (int kt = 1; kt < 16; kt++) kstep(FalseT{});
        wg_wait<0>();
        if (threadIdx.x == 0) TS(4, 3);
        fence_regs<BN / 2>(acc);
        bar_sync(3, 256);
        const uint32_t stg = sb + wg * (BN / 64) * 8192;
        const int strow = warp * 16 + (lane & 7) + ((lane >> 3) & 1) * 8;
        const uint32_t st_base = stg + strow * 128;
        const uint32_t st_x = strow & 7, st_c = lane >> 4;
#pragma unroll
        for (int b = 0; b < BN / 64; b++) {
#pragma unroll
            for (int jj = 0; jj < 4; jj++) {
                const int j = b * 8 + jj * 2;
                stsm_x4(st_base + b * 8192 + (((jj * 2 + st_c) ^ st_x) << 4),
                        pack_bf16(acc[4 * j], acc[4 * j + 1]), pack_bf16(acc[4 * j + 2], acc[4 * j + 3]),
                        pack_bf16(acc[4 * j + 4], acc[4 * j + 5]), pack_bf16(acc[4 * j + 6], acc[4 * j + 7]));
            }
        }
        fence_async_smem();
        bar_sync(1 + wg, 128);
        if (warp == 0 && lane == 0) {
#pragma unroll
            for (int b = 0; b < BN / 64; b++) tma_store(&tm.out, stg + b * 8192, prob * DM + nt * BN + b * 64, mt * 128 + wg * 64);
            bulk_commit();
            bulk_wait<0>();
            if (threadIdx.x == 0) TS(4, 4);
        }
    }
}

template <int MASK8> __device__ __forceinline__ void exp_pack8(const float* s, uint32_t* p) {
#pragma unroll
    for (int i = 0; i < 4; i++) {
        float a = s[2 * i], b = s[2 * i + 1];
        a = ((MASK8 >> (2 * i)) & 1) ? ex2_poly(a) : ex2(a);
        b = ((MASK8 >> (2 * i + 1)) & 1) ? ex2_poly(b) : ex2(b);
        p[i] = pack_bf16(a, b);
    }
}

template <int NWG, int KVST> struct AttCfg {
    static constexpr int THREADS = NWG * 128;
    static constexpr int QROWS = NWG * 64;
    static constexpr int KV_STAGE = 16384;
    static constexpr int OFF_Q = KVST * KV_STAGE;
    static constexpr int OFF_ONES = OFF_Q + 2 * QROWS * 64;
    static constexpr int OFF_BAR = OFF_ONES + 1024;
    static constexpr int SMEM = OFF_BAR + 256 + 1024;
    static constexpr int NTASK = NH * (SEQ / QROWS);
};

constexpr float SAFE_BOUND = 90.0f;

template <int NWG, int KVST, int MASK16, int W1, int MINB>
__global__ void __launch_bounds__(NWG * 128, MINB)
attn_kernel(const __grid_constant__ TMaps tm) {
    using C = AttCfg<NWG, KVST>;
    extern __shared__ uint8_t smem_raw[];
    const uint32_t sb = (smem_u32(smem_raw) + 1023) & ~1023u;
    const uint32_t bar_full = sb + C::OFF_BAR, bar_empty = bar_full + 8 * KVST;
    const uint32_t bar_qfull = bar_empty + 8 * KVST, bar_qempty = bar_qfull + 16;
    const int wg = __shfl_sync(0xffffffffu, threadIdx.x >> 7, 0);
    const int warp = __shfl_sync(0xffffffffu, (threadIdx.x >> 5) & 3, 0), lane = threadIdx.x & 31;

    if (threadIdx.x == 0) {
        for (int s = 0; s < KVST; s++) { mbar_init(bar_full + 8 * s, 1); mbar_init(bar_empty + 8 * s, NWG * 4); }
        for (int s = 0; s < 2; s++) { mbar_init(bar_qfull + 8 * s, 1); mbar_init(bar_qempty + 8 * s, NWG * 4); }
        fence_mbar_init();
        prefetch_tmap(&tm.qkv128);
    }
    if (threadIdx.x < 64) {
        asm volatile("st.shared.v4.b32 [%0], {%1, %2, %2, %2};" ::"r"(sb + C::OFF_ONES + threadIdx.x * 16), "r"(0x00003F80u), "r"(0u) : "memory");
        fence_async_smem();
    }
    __syncthreads();
    pdl_launch();
    pdl_wait();
    if (threadIdx.x == 0) { TS(3, 0); TSC(5, 2); }

    int pr_s = 0, pr_qs = 0, pr_st = 0, pr_t = blockIdx.x;
    uint32_t pr_ph = 1, pr_qph = 1;
    const bool is_prod = (wg == 0 && warp == 0);
    auto produce = [&]() {
        if (pr_t < C::NTASK) {
            if (is_prod) {
                const int h = pr_t / (SEQ / C::QROWS), qt = pr_t % (SEQ / C::QROWS);
                if (pr_st == 0) {
                    mbar_wait(bar_qempty + 8 * pr_qs, pr_qph);
                    mbar_expect_tx_l0(bar_qfull + 8 * pr_qs, C::QROWS * 64);
                    const int rowQ = ((3 + 0) * NH + h) * SEQ + qt * C::QROWS;
#pragma unroll
                    for (int i = 0; i < C::QROWS / 128; i++)
                        tma_load_l0(sb + C::OFF_Q + pr_qs * C::QROWS * 64 + i * 8192, &tm.qkv128, bar_qfull + 8 * pr_qs, 0, rowQ + i * 128);
                }
                mbar_wait(bar_empty + 8 * pr_s, pr_ph);
                const uint32_t dst = sb + pr_s * C::KV_STAGE, fb = bar_full + 8 * pr_s;
                mbar_expect_tx_l0(fb, C::KV_STAGE);
                tma_load_l0(dst, &tm.qkv128, fb, 0, ((3 + 1) * NH + h) * SEQ + pr_st * 128);
                tma_load_l0(dst + 8192, &tm.qkv128, fb, 0, ((3 + 2) * NH + h) * SEQ + pr_st * 128);
            }
            if (pr_st == 0) { if (++pr_qs == 2) { pr_qs = 0; pr_qph ^= 1; } }
            if (++pr_s == KVST) { pr_s = 0; pr_ph ^= 1; }
            if (++pr_st == 16) { pr_st = 0; pr_t += gridDim.x; }
        }
    };
#pragma unroll 1
    for (int i = 0; i < KVST - 1; i++) produce();

    int s = 0, qs = 0;
    uint32_t ph = 0, qph = 0;
    const int qrow = wg * 64 + warp * 16 + (lane & 7) + ((lane >> 3) & 1) * 8;
    constexpr uint32_t DV_STEP = 64u - (64u << 16);
    const uint32_t k_lo0 = desc_lo(sb, 16);
    const uint32_t v_lo0 = desc_lo(sb + 8192, C::OFF_ONES - 8192);
    constexpr uint32_t V_STAGE_STEP = 1024u - (1024u << 16);
    for (int t = blockIdx.x; t < C::NTASK; t += gridDim.x) {
        const int h = t / (SEQ / C::QROWS), qt = t % (SEQ / C::QROWS);
        int fast;
        {
            float qm = 0.f, km = 0.f, vm = 0.f;
#pragma unroll
            for (int i = 0; i < 4; i++) {
                qm = nanmax(qm, g_norm[(0 * NH + h) * 128 + lane + 32 * i]);
                km = nanmax(km, g_norm[(1 * NH + h) * 128 + lane + 32 * i]);
                vm = nanmax(vm, g_norm[(2 * NH + h) * 128 + lane + 32 * i]);
            }
#pragma unroll
            for (int o = 1; o < 32; o <<= 1) {
                qm = nanmax(qm, __shfl_xor_sync(0xffffffffu, qm, o));
                km = nanmax(km, __shfl_xor_sync(0xffffffffu, km, o));
                vm = nanmax(vm, __shfl_xor_sync(0xffffffffu, vm, o));
            }
            const int okf = (qm * km * 1.05f <= SAFE_BOUND * SAFE_BOUND) && (qm < 1e30f) && (km < 1e30f) &&
                            (vm >= 0.0009765625f) && (vm <= 1048576.f);
            fast = __shfl_sync(0xffffffffu, okf, 0);
        }
        uint32_t q[8];
        mbar_wait(bar_qfull + 8 * qs, qph);
        {
            const uint32_t qa = sb + C::OFF_Q + qs * C::QROWS * 64 + qrow * 64;
            const uint32_t x = (qrow >> 1) & 3, c = lane >> 4;
            ldsm_x4(qa + (((0 + c) ^ x) << 4), q[0], q[1], q[2], q[3]);
            ldsm_x4(qa + (((2 + c) ^ x) << 4), q[4], q[5], q[6], q[7]);
        }
        fence_regs_u<8>(q);
        __syncwarp();
        mbar_arrive_lane0(bar_qempty + 8 * qs);
        if (++qs == 2) { qs = 0; qph ^= 1; }

        float o[20];
#pragma unroll
        for (int i = 0; i < 20; i++) o[i] = 0.f;
        fence_regs<20>(o);

        if (fast) {
            float s0[32], s1[32];
            uint32_t p0[16], p1_[16];
            uint32_t* p1 = W1 ? p1_ : p0;
            auto qk = [&](float* sc, uint32_t dK) {
                wg_fence();
                wg_rs64_z(sc, q[0], q[1], q[2], q[3], dK);
                wg_rs64(sc, q[4], q[5], q[6], q[7], dK + 2);
                wg_commit();
            };
            auto exp_pv = [&](const float* sc, uint32_t* p, uint32_t dV) {
#pragma unroll
                for (int kk = 0; kk < 4; kk++) {
                    if (kk & 1) exp_pack8<(MASK16 >> 8) & 0xFF>(sc + 8 * kk, p + 4 * kk);
                    else exp_pack8<MASK16 & 0xFF>(sc + 8 * kk, p + 4 * kk);
                    wg_fence();
                    wg_rs40t(o, p[4 * kk], p[4 * kk + 1], p[4 * kk + 2], p[4 * kk + 3], dV + kk * DV_STEP);
                }
                wg_commit();
            };
            mbar_wait(bar_full + 8 * s, ph);
            qk(s0, k_lo0 + s * 1024);
            wg_wait<0>();
            fence_regs<32>(s0);
            int sprev = s;
#pragma unroll 1
            for (int st = 0; st < 15; st++) {
                const uint32_t dK = k_lo0 + s * 1024, dV = v_lo0 + s * V_STAGE_STEP;
                qk(s1, dK + 256);
                exp_pv(s0, p0, dV);
                if (W1) wg_wait<1>(); else wg_wait<0>();
                fence_regs<32>(s1);
                if (W1) { if (st > 0) mbar_arrive_lane0(bar_empty + 8 * sprev); }
                sprev = s;
                if (++s == KVST) { s = 0; ph ^= 1; }
                mbar_wait(bar_full + 8 * s, ph);
                qk(s0, k_lo0 + s * 1024);
                exp_pv(s1, p1, dV + 4 * DV_STEP);
                if (W1) wg_wait<1>(); else wg_wait<0>();
                fence_regs<32>(s0);
                if (!W1) mbar_arrive_lane0(bar_empty + 8 * sprev);
                produce();
            }
            {
                const uint32_t dK = k_lo0 + s * 1024, dV = v_lo0 + s * V_STAGE_STEP;
                qk(s1, dK + 256);
                exp_pv(s0, p0, dV);
                if (W1) wg_wait<1>(); else wg_wait<0>();
                fence_regs<32>(s1);
                if (W1) mbar_arrive_lane0(bar_empty + 8 * sprev);
                exp_pv(s1, p1, dV + 4 * DV_STEP);
                wg_wait<0>();
                fence_regs<20>(o);
                mbar_arrive_lane0(bar_empty + 8 * s);
                if (++s == KVST) { s = 0; ph ^= 1; }
                produce();
            }
        } else {
            float sc[32];
            uint32_t p[16];
            float m0 = -INFINITY, m1 = -INFINITY;
#pragma unroll 1
            for (int st = 0; st < 16; st++) {
                mbar_wait(bar_full + 8 * s, ph);
                const uint32_t dK = k_lo0 + s * 1024, dV = v_lo0 + s * V_STAGE_STEP;
#pragma unroll 1
                for (int sub = 0; sub < 2; sub++) {
                    wg_fence();
                    wg_rs64_z(sc, q[0], q[1], q[2], q[3], dK + sub * 256);
                    wg_rs64(sc, q[4], q[5], q[6], q[7], dK + sub * 256 + 2);
                    wg_commit();
                    wg_wait<0>();
                    fence_regs<32>(sc);
                    float x0 = m0, x1 = m1;
#pragma unroll
                    for (int j = 0; j < 8; j++) {
                        x0 = fmaxf(x0, fmaxf(sc[4 * j], sc[4 * j + 1]));
                        x1 = fmaxf(x1, fmaxf(sc[4 * j + 2], sc[4 * j + 3]));
                    }
                    x0 = fmaxf(x0, __shfl_xor_sync(0xffffffffu, x0, 1)); x0 = fmaxf(x0, __shfl_xor_sync(0xffffffffu, x0, 2));
                    x1 = fmaxf(x1, __shfl_xor_sync(0xffffffffu, x1, 1)); x1 = fmaxf(x1, __shfl_xor_sync(0xffffffffu, x1, 2));
                    const float al0 = ex2(m0 - x0), al1 = ex2(m1 - x1);
                    m0 = x0; m1 = x1;
#pragma unroll
                    for (int j = 0; j < 5; j++) { o[4 * j] *= al0; o[4 * j + 1] *= al0; o[4 * j + 2] *= al1; o[4 * j + 3] *= al1; }
#pragma unroll
                    for (int j = 0; j < 8; j++) {
                        p[2 * j] = pack_bf16(ex2(sc[4 * j] - x0), ex2(sc[4 * j + 1] - x0));
                        p[2 * j + 1] = pack_bf16(ex2(sc[4 * j + 2] - x1), ex2(sc[4 * j + 3] - x1));
                    }
                    fence_regs<20>(o); fence_regs_u<16>(p);
                    wg_fence();
#pragma unroll
                    for (int kk = 0; kk < 4; kk++) wg_rs40t(o, p[4 * kk], p[4 * kk + 1], p[4 * kk + 2], p[4 * kk + 3], dV + (sub * 4 + kk) * DV_STEP);
                    wg_commit();
                    wg_wait<0>();
                    fence_regs<20>(o);
                }
                mbar_arrive_lane0(bar_empty + 8 * s);
                produce();
                if (++s == KVST) { s = 0; ph ^= 1; }
            }
        }
        const float l0 = __shfl_sync(0xffffffffu, o[16], lane & ~3), l1 = __shfl_sync(0xffffffffu, o[18], lane & ~3);
        const float i0 = 1.0f / l0, i1 = 1.0f / l1;
        const int tok = qt * C::QROWS + wg * 64 + warp * 16 + (lane >> 2);
        uint32_t* dst = reinterpret_cast<uint32_t*>(g_o + (size_t)(SEQ + tok) * DM + h * 32 + (lane & 3) * 2);
#pragma unroll
        for (int j = 0; j < 4; j++) {
            dst[j * 4] = pack_bf16(o[4 * j] * i0, o[4 * j + 1] * i0);
            dst[j * 4 + 8 * (DM / 2)] = pack_bf16(o[4 * j + 2] * i1, o[4 * j + 3] * i1);
        }
        if (threadIdx.x == 0) { TS(3, t < (int)gridDim.x ? 1 : (t < 2 * (int)gridDim.x ? 2 : 3)); TSC(5, t < (int)gridDim.x ? 3 : 4); }
    }
}

__device__ __forceinline__ void hedgehog_row(const uint4 raw, uint32_t* pos, uint32_t* neg) {
    float x[8];
    const uint32_t w[4] = {raw.x, raw.y, raw.z, raw.w};
#pragma unroll
    for (int i = 0; i < 4; i++) { x[2 * i] = __uint_as_float(w[i] << 16); x[2 * i + 1] = __uint_as_float(w[i] & 0xffff0000u); }
    float mx = x[0], mn = x[0];
#pragma unroll
    for (int i = 1; i < 8; i++) { mx = fmaxf(mx, x[i]); mn = fminf(mn, x[i]); }
    mx = fmaxf(mx, __shfl_xor_sync(0xffffffffu, mx, 1)); mn = fminf(mn, __shfl_xor_sync(0xffffffffu, mn, 1));
    mx = fmaxf(mx, __shfl_xor_sync(0xffffffffu, mx, 2)); mn = fminf(mn, __shfl_xor_sync(0xffffffffu, mn, 2));
    constexpr float L2E = 1.4426950408889634f;
    const float mxs = -mx * L2E, mns = mn * L2E;
    float ep[8], en[8], sp = 0.f, sn = 0.f;
#pragma unroll
    for (int i = 0; i < 8; i++) {
        ep[i] = ex2(fmaf(x[i], L2E, mxs));
        en[i] = ex2(fmaf(x[i], -L2E, mns));
        sp += ep[i]; sn += en[i];
    }
    sp += __shfl_xor_sync(0xffffffffu, sp, 1); sn += __shfl_xor_sync(0xffffffffu, sn, 1);
    sp += __shfl_xor_sync(0xffffffffu, sp, 2); sn += __shfl_xor_sync(0xffffffffu, sn, 2);
    const float ip = 1.0f / sp, in = 1.0f / sn;
#pragma unroll
    for (int i = 0; i < 4; i++) {
        pos[i] = pack_bf16(ep[2 * i] * ip, ep[2 * i + 1] * ip);
        neg[i] = pack_bf16(en[2 * i] * in, en[2 * i + 1] * in);
    }
}

__global__ void __launch_bounds__(128) lin_kv_kernel() {
    __shared__ __align__(1024) uint8_t sm[8192 + 4096 + 1024];
    const uint32_t sphi = smem_u32(sm), sv = sphi + 8192, sones = sv + 4096;
    const int h = blockIdx.x >> 3, ch = blockIdx.x & 7;
    const int warp = threadIdx.x >> 5, lane = threadIdx.x & 31;
    const int r = lane >> 2, c = lane & 3;
    if (threadIdx.x < 64) asm volatile("st.shared.v4.b32 [%0], {%1, %2, %2, %2};" ::"r"(sones + threadIdx.x * 16), "r"(0x00003F80u), "r"(0u) : "memory");
    pdl_launch();
    pdl_wait();
    if (threadIdx.x == 0) TS(1, 0);
    const __nv_bfloat16* gk = g_qkv + (size_t)((0 * 3 + 1) * NH + h) * SEQ * 32;
    const __nv_bfloat16* gv = g_qkv + (size_t)((0 * 3 + 2) * NH + h) * SEQ * 32;
    float acc[20];
#pragma unroll
    for (int i = 0; i < 20; i++) acc[i] = 0.f;
    fence_regs<20>(acc);
    const uint32_t dA = desc_lo(sphi, 16);
    const uint32_t dB = desc_lo(sv, sones - sv);
    const uint32_t DV_STEP = 64u - (64u << 16);
#pragma unroll 1
    for (int mb = 0; mb < 4; mb++) {
        const int tok0 = ch * 256 + mb * 64;
        const int row0 = warp * 16 + r;
        const uint4 k0 = *reinterpret_cast<const uint4*>(gk + (size_t)(tok0 + row0) * 32 + c * 8);
        const uint4 k1 = *reinterpret_cast<const uint4*>(gk + (size_t)(tok0 + row0 + 8) * 32 + c * 8);
        uint4 vv[2];
#pragma unroll
        for (int i = 0; i < 2; i++) {
            const int idx = threadIdx.x + 128 * i;
            vv[i] = *reinterpret_cast<const uint4*>(gv + (size_t)tok0 * 32 + idx * 8);
        }
        uint32_t pos0[4], neg0[4], pos1[4], neg1[4];
        hedgehog_row(k0, pos0, neg0);
        hedgehog_row(k1, pos1, neg1);
        if (mb > 0) __syncthreads();
        {
            const int ra = row0, rb = row0 + 8;
            asm volatile("st.shared.v4.b32 [%0], {%1, %2, %3, %4};" ::"r"(sphi + ra * 128 + ((c ^ (ra & 7)) << 4)), "r"(pos0[0]), "r"(pos0[1]), "r"(pos0[2]), "r"(pos0[3]) : "memory");
            asm volatile("st.shared.v4.b32 [%0], {%1, %2, %3, %4};" ::"r"(sphi + ra * 128 + (((4 + c) ^ (ra & 7)) << 4)), "r"(neg0[0]), "r"(neg0[1]), "r"(neg0[2]), "r"(neg0[3]) : "memory");
            asm volatile("st.shared.v4.b32 [%0], {%1, %2, %3, %4};" ::"r"(sphi + rb * 128 + ((c ^ (rb & 7)) << 4)), "r"(pos1[0]), "r"(pos1[1]), "r"(pos1[2]), "r"(pos1[3]) : "memory");
            asm volatile("st.shared.v4.b32 [%0], {%1, %2, %3, %4};" ::"r"(sphi + rb * 128 + (((4 + c) ^ (rb & 7)) << 4)), "r"(neg1[0]), "r"(neg1[1]), "r"(neg1[2]), "r"(neg1[3]) : "memory");
#pragma unroll
            for (int i = 0; i < 2; i++) {
                const int idx = threadIdx.x + 128 * i, vr = idx >> 2, vc = idx & 3;
                asm volatile("st.shared.v4.b32 [%0], {%1, %2, %3, %4};" ::"r"(sv + vr * 64 + ((vc ^ ((vr >> 1) & 3)) << 4)), "r"(vv[i].x), "r"(vv[i].y), "r"(vv[i].z), "r"(vv[i].w) : "memory");
            }
        }
        fence_async_smem();
        __syncthreads();
        wg_fence();
#pragma unroll
        for (int kk = 0; kk < 4; kk++) wg_ss40tt(acc, dA + kk * 128, dB + kk * DV_STEP);
        wg_commit();
        wg_wait<0>();
        fence_regs<20>(acc);
    }
    if (threadIdx.x == 0) TS(1, 1);
    float* dst = g_kvp + (size_t)(h * 8 + ch) * 2560 + (warp * 16 + r) * 40 + c * 2;
#pragma unroll
    for (int j = 0; j < 5; j++) {
        *reinterpret_cast<float2*>(dst + j * 8) = make_float2(acc[4 * j], acc[4 * j + 1]);
        *reinterpret_cast<float2*>(dst + 8 * 40 + j * 8) = make_float2(acc[4 * j + 2], acc[4 * j + 3]);
    }
}

__global__ void __launch_bounds__(128) lin_out_kernel() {
    __shared__ __align__(1024) uint8_t sm[8192];
    const uint32_t skv = smem_u32(sm);
    const int h = blockIdx.x >> 3, ch = blockIdx.x & 7;
    const int warp = threadIdx.x >> 5, lane = threadIdx.x & 31;
    const int r = lane >> 2, c = lane & 3;
    pdl_launch();
    pdl_wait();
    if (threadIdx.x == 0) TS(2, 0);
    for (int idx = threadIdx.x; idx < 320; idx += 128) {
        const int f = idx / 5, cg = idx % 5;
        float sum[8];
#pragma unroll
        for (int i = 0; i < 8; i++) sum[i] = 0.f;
#pragma unroll
        for (int pp = 0; pp < 8; pp++) {
            const float4* src = reinterpret_cast<const float4*>(g_kvp + (size_t)(h * 8 + pp) * 2560 + f * 40 + cg * 8);
            const float4 a = src[0], b = src[1];
            sum[0] += a.x; sum[1] += a.y; sum[2] += a.z; sum[3] += a.w; sum[4] += b.x; sum[5] += b.y; sum[6] += b.z; sum[7] += b.w;
        }
        const int half = f >> 5, cc = (f >> 3) & 3, i = f & 7;
        const int kp = half * 32 + 16 * (i >> 2) + 8 * ((i >> 1) & 1) + 2 * cc + (i & 1);
        const uint32_t a = skv + (cg == 4 ? 4096 : 0) + kp * 64 + (((cg & 3) ^ ((kp >> 1) & 3)) << 4);
        asm volatile("st.shared.v4.b32 [%0], {%1, %2, %3, %4};" ::"r"(a), "r"(pack_bf16(sum[0], sum[1])), "r"(pack_bf16(sum[2], sum[3])),
                     "r"(pack_bf16(sum[4], sum[5])), "r"(pack_bf16(sum[6], sum[7])) : "memory");
    }
    fence_async_smem();
    __syncthreads();
    const __nv_bfloat16* gq = g_qkv + (size_t)((0 * 3 + 0) * NH + h) * SEQ * 32;
    const uint32_t dB = desc_lo(skv, 4096);
#pragma unroll 1
    for (int mb = 0; mb < 4; mb++) {
        const int tok = ch * 256 + mb * 64 + warp * 16 + r;
        const uint4 q0 = *reinterpret_cast<const uint4*>(gq + (size_t)tok * 32 + c * 8);
        const uint4 q1 = *reinterpret_cast<const uint4*>(gq + (size_t)(tok + 8) * 32 + c * 8);
        uint32_t pos0[4], neg0[4], pos1[4], neg1[4];
        hedgehog_row(q0, pos0, neg0);
        hedgehog_row(q1, pos1, neg1);
        float acc[20];
        fence_regs_u<4>(pos0); fence_regs_u<4>(pos1); fence_regs_u<4>(neg0); fence_regs_u<4>(neg1);
        wg_fence();
        wg_rs40t_z(acc, pos0[0], pos1[0], pos0[1], pos1[1], dB);
        wg_rs40t(acc, pos0[2], pos1[2], pos0[3], pos1[3], dB + 64);
        wg_rs40t(acc, neg0[0], neg1[0], neg0[1], neg1[1], dB + 128);
        wg_rs40t(acc, neg0[2], neg1[2], neg0[3], neg1[3], dB + 192);
        wg_commit();
        wg_wait<0>();
        fence_regs<20>(acc);
        const float d0 = __shfl_sync(0xffffffffu, acc[16], lane & ~3) + 1e-6f, d1 = __shfl_sync(0xffffffffu, acc[18], lane & ~3) + 1e-6f;
        const float i0 = 1.0f / d0, i1 = 1.0f / d1;
        uint32_t* dst = reinterpret_cast<uint32_t*>(g_o + (size_t)tok * DM + h * 32 + c * 2);
#pragma unroll
        for (int j = 0; j < 4; j++) {
            dst[j * 4] = pack_bf16(acc[4 * j] * i0, acc[4 * j + 1] * i0);
            dst[j * 4 + 8 * (DM / 2)] = pack_bf16(acc[4 * j + 2] * i1, acc[4 * j + 3] * i1);
        }
    }
    if (threadIdx.x == 0) TS(2, 1);
}

typedef CUresult (*EncodeFn)(CUtensorMap*, CUtensorMapDataType, cuuint32_t, void*, const cuuint64_t*, const cuuint64_t*,
                             const cuuint32_t*, const cuuint32_t*, CUtensorMapInterleave, CUtensorMapSwizzle,
                             CUtensorMapL2promotion, CUtensorMapFloatOOBfill);

void make_map(EncodeFn enc, CUtensorMap* m, const void* ptr, uint64_t d0, uint64_t d1, uint32_t b0, uint32_t b1, CUtensorMapSwizzle sw) {
    cuuint64_t dims[2] = {d0, d1};
    cuuint64_t strides[1] = {d0 * 2};
    cuuint32_t box[2] = {b0, b1};
    cuuint32_t es[2] = {1, 1};
    enc(m, CU_TENSOR_MAP_DATA_TYPE_BFLOAT16, 2, const_cast<void*>(ptr), dims, strides, box, es, CU_TENSOR_MAP_INTERLEAVE_NONE, sw,
        CU_TENSOR_MAP_L2_PROMOTION_L2_128B, CU_TENSOR_MAP_FLOAT_OOB_FILL_NONE);
}

template <typename... KArgs, typename... Args>
void launch(void (*k)(KArgs...), int grid, int block, int smem, cudaStream_t st, bool pdl, Args... args) {
    cudaLaunchConfig_t cfg = {};
    cfg.gridDim = dim3(grid); cfg.blockDim = dim3(block); cfg.dynamicSmemBytes = smem; cfg.stream = st;
    cudaLaunchAttribute at[1];
    at[0].id = cudaLaunchAttributeProgrammaticStreamSerialization;
    at[0].val.programmaticStreamSerializationAllowed = 1;
    cfg.attrs = at; cfg.numAttrs = pdl ? 1 : 0;
    cudaLaunchKernelEx(&cfg, k, KArgs(args)...);
}

constexpr int K1_MB = 2, K1_ST = 3;
constexpr int K3_BN = 256, K3_ST = 4;
constexpr int K2_NWG = 4, K2_KVST = 4, K2_MASK = 0x1111, K2_W1 = 0;

}

extern "C" void kernel_launch(void* const* d_in, const int* in_sizes, int n_in, void* d_out, int out_size) {
    (void)in_sizes; (void)n_in; (void)out_size;
    static bool init = false;
    static TMaps tm;
    static int nsm = 132;
    static void* cached[8];
    auto k1 = qkv_gemm_kernel<K1_MB, K1_ST, 240, 24>;
    auto k2 = attn_kernel<K2_NWG, K2_KVST, K2_MASK, K2_W1, 1>;
    auto k3 = out_gemm_kernel<K3_BN, K3_ST, 232, 40>;
    bool same = init;
    for (int i = 0; i < 7 && same; i++) same = cached[i] == d_in[i];
    same = same && cached[7] == d_out;
    if (!same) {
        void* fn = nullptr;
        cudaDriverEntryPointQueryResult qr;
        cudaGetDriverEntryPoint("cuTensorMapEncodeTiled", &fn, cudaEnableDefault, &qr);
        EncodeFn enc = (EncodeFn)fn;
        void *pqkv, *po;
        cudaGetSymbolAddress(&pqkv, g_qkv);
        cudaGetSymbolAddress(&po, g_o);
        make_map(enc, &tm.x[0], d_in[0], 1024, 2048, 64, 128 * K1_MB, CU_TENSOR_MAP_SWIZZLE_128B);
        make_map(enc, &tm.x[1], d_in[4], 1024, 2048, 64, 128 * K1_MB, CU_TENSOR_MAP_SWIZZLE_128B);
        make_map(enc, &tm.w[0], d_in[1], 3072, 1024, 64, 64, CU_TENSOR_MAP_SWIZZLE_128B);
        make_map(enc, &tm.w[1], d_in[5], 3072, 1024, 64, 64, CU_TENSOR_MAP_SWIZZLE_128B);
        make_map(enc, &tm.phi, d_in[2], 32, 1024, 32, 64, CU_TENSOR_MAP_SWIZZLE_64B);
        make_map(enc, &tm.qkv64, pqkv, 32, 2 * 3 * NH * SEQ, 32, 64, CU_TENSOR_MAP_SWIZZLE_64B);
        make_map(enc, &tm.qkv128, pqkv, 32, 2 * 3 * NH * SEQ, 32, 128, CU_TENSOR_MAP_SWIZZLE_64B);
        make_map(enc, &tm.o, po, 1024, 2 * SEQ, 64, 128, CU_TENSOR_MAP_SWIZZLE_128B);
        make_map(enc, &tm.wo[0], d_in[3], 1024, 1024, 64, 64, CU_TENSOR_MAP_SWIZZLE_128B);
        make_map(enc, &tm.wo[1], d_in[6], 1024, 1024, 64, 64, CU_TENSOR_MAP_SWIZZLE_128B);
        make_map(enc, &tm.out, d_out, 2048, 2048, 64, 64, CU_TENSOR_MAP_SWIZZLE_128B);
        cudaFuncSetAttribute(k1, cudaFuncAttributeMaxDynamicSharedMemorySize, QkvCfg<K1_MB, K1_ST>::SMEM);
        cudaFuncSetAttribute(k2, cudaFuncAttributeMaxDynamicSharedMemorySize, AttCfg<K2_NWG, K2_KVST>::SMEM);
        cudaFuncSetAttribute(k3, cudaFuncAttributeMaxDynamicSharedMemorySize, OutCfg<K3_BN, K3_ST>::SMEM);
        int dev = 0;
        cudaGetDevice(&dev);
        cudaDeviceGetAttribute(&nsm, cudaDevAttrMultiProcessorCount, dev);
        for (int i = 0; i < 7; i++) cached[i] = d_in[i];
        cached[7] = d_out;
        init = true;
    }
    cudaStream_t st = cudaStreamPerThread;
    const int ntile = 2 * QkvCfg<K1_MB, K1_ST>::TPP;
    launch(k1, ntile < nsm ? ntile : nsm, 384, QkvCfg<K1_MB, K1_ST>::SMEM, st, false, tm, 0, ntile, 1);
    launch(lin_kv_kernel, 256, 128, 0, st, true);
    launch(lin_out_kernel, 256, 128, 0, st, true);
    const int ntask = AttCfg<K2_NWG, K2_KVST>::NTASK;
    launch(k2, ntask < nsm ? ntask : nsm, AttCfg<K2_NWG, K2_KVST>::THREADS, AttCfg<K2_NWG, K2_KVST>::SMEM, st, true, tm);
    launch(k3, 2 * 16 * OutCfg<K3_BN, K3_ST>::NT, 384, OutCfg<K3_BN, K3_ST>::SMEM, st, true, tm, 0);
}
```

```cpp
#include <cuda_runtime.h>
#include <cuda_bf16.h>
#include <cuda.h>
#include <stdint.h>

namespace {

constexpr int SEQ = 2048;
constexpr int DM = 1024;
constexpr int NH = 32;

__device__ __align__(1024) __nv_bfloat16 g_qkv[2 * 3 * NH * SEQ * 32];
__device__ __align__(1024) __nv_bfloat16 g_o[2 * SEQ * DM];
__device__ float g_norm[3 * NH * 128];
__device__ __align__(16) float g_kv[2 * NH * 64 * 40];

constexpr int CS = 8;
struct Sync {
    uint32_t epoch, pad0[31];
    uint32_t done, pad1[31];
    uint32_t cntB[16 * CS];
    uint32_t flagB[NH * CS];
    uint32_t cntA[16 * 8 * CS];
    uint32_t cntL1[NH * CS];
    uint32_t cntOA[8 * CS];
    uint32_t cntOB[2 * 16 * CS];
};
__device__ Sync g_sync;

struct TMaps {
    CUtensorMap x[2];
    CUtensorMap w[2];
    CUtensorMap phi;
    CUtensorMap o;
    CUtensorMap ost;
    CUtensorMap wo[2];
};

__device__ __forceinline__ uint32_t smem_u32(const void* p) { return (uint32_t)__cvta_generic_to_shared(p); }
__device__ __forceinline__ void mbar_init(uint32_t bar, uint32_t cnt) {
    asm volatile("mbarrier.init.shared::cta.b64 [%0], %1;" ::"r"(bar), "r"(cnt) : "memory");
}
__device__ __forceinline__ void mbar_wait(uint32_t bar, uint32_t parity) {
    asm volatile(
        "{\n"
        ".reg .pred p;\n"
        ".reg .u32 n;\n"
        "mbarrier.try_wait.parity.shared::cta.b64 p, [%0], %1;\n"
        "@p bra DONE;\n"
        "mov.u32 n, 0;\n"
        "LAB_WAIT:\n"
        "mbarrier.try_wait.parity.shared::cta.b64 p, [%0], %1, 20000;\n"
        "@p bra DONE;\n"
        "add.u32 n, n, 1;\n"
        "setp.lt.u32 p, n, 400000;\n"
        "@p bra LAB_WAIT;\n"
        "trap;\n"
        "DONE:\n"
        "}\n" ::"r"(bar), "r"(parity) : "memory");
}
__device__ __forceinline__ void tma_load_l0(uint32_t dst, const CUtensorMap* m, uint32_t bar, int c0, int c1) {
    asm volatile("{\n.reg .pred p;\nelect.sync _|p, 0xffffffff;\n"
                 "@p cp.async.bulk.tensor.2d.shared::cluster.global.mbarrier::complete_tx::bytes [%0], [%1, {%3, %4}], [%2];\n}"
                 ::"r"(dst), "l"(m), "r"(bar), "r"(c0), "r"(c1) : "memory");
}
__device__ __forceinline__ void bulk_load_l0(uint32_t dst, const void* src, uint32_t bytes, uint32_t bar) {
    asm volatile("{\n.reg .pred p;\nelect.sync _|p, 0xffffffff;\n"
                 "@p cp.async.bulk.shared::cluster.global.mbarrier::complete_tx::bytes [%0], [%1], %2, [%3];\n}"
                 ::"r"(dst), "l"(src), "r"(bytes), "r"(bar) : "memory");
}
__device__ __forceinline__ void mbar_expect_tx_noarrive_l0(uint32_t bar, uint32_t bytes) {
    asm volatile("{\n.reg .pred p;\nelect.sync _|p, 0xffffffff;\n"
                 "@p mbarrier.expect_tx.relaxed.cta.shared::cta.b64 [%0], %1;\n}" ::"r"(bar), "r"(bytes) : "memory");
}
__device__ __forceinline__ void mbar_expect_tx_l0(uint32_t bar, uint32_t bytes) {
    asm volatile("{\n.reg .pred p;\nelect.sync _|p, 0xffffffff;\n"
                 "@p mbarrier.arrive.expect_tx.shared::cta.b64 _, [%0], %1;\n}" ::"r"(bar), "r"(bytes) : "memory");
}
__device__ __forceinline__ void prefetch_tmap(const CUtensorMap* m) { asm volatile("prefetch.tensormap [%0];" ::"l"(m) : "memory"); }
__device__ __forceinline__ void fence_async_smem() { asm volatile("fence.proxy.async.shared::cta;" ::: "memory"); }
__device__ __forceinline__ void fence_mbar_init() { asm volatile("fence.mbarrier_init.release.cluster;" ::: "memory"); }
__device__ __forceinline__ void bar_sync(int id, int n) { asm volatile("bar.sync %0, %1;" ::"r"(id), "r"(n) : "memory"); }
__device__ __forceinline__ void bar_arrive(int id, int n) { asm volatile("bar.arrive %0, %1;" ::"r"(id), "r"(n) : "memory"); }
__device__ __forceinline__ void wg_fence() { asm volatile("wgmma.fence.sync.aligned;" ::: "memory"); }
__device__ __forceinline__ void wg_commit() { asm volatile("wgmma.commit_group.sync.aligned;" ::: "memory"); }
template <int N> __device__ __forceinline__ void wg_wait() { asm volatile("wgmma.wait_group.sync.aligned %0;" ::"n"(N) : "memory"); }
template <int N> __device__ __forceinline__ void fence_regs(float* d) {
#pragma unroll
    for (int i = 0; i < N; i++) asm volatile("" : "+f"(d[i])::"memory");
}
template <int N> __device__ __forceinline__ void fence_regs_u(uint32_t* d) {
#pragma unroll
    for (int i = 0; i < N; i++) asm volatile("" : "+r"(d[i])::"memory");
}
__device__ __forceinline__ uint32_t desc_lo(uint32_t addr, uint32_t lbo) { return ((addr & 0x3FFFF) >> 4) | ((lbo >> 4) << 16); }
__device__ __forceinline__ void mbar_arrive_lane0(uint32_t bar) {
    asm volatile("{\n.reg .pred p;\nelect.sync _|p, 0xffffffff;\n@p mbarrier.arrive.shared::cta.b64 _, [%0];\n}" ::"r"(bar) : "memory");
}
__device__ __forceinline__ uint32_t pack_bf16(float lo, float hi) {
    uint32_t r;
    asm("cvt.rn.bf16x2.f32 %0, %1, %2;" : "=r"(r) : "f"(hi), "f"(lo));
    return r;
}
__device__ __forceinline__ void stsm_x4(uint32_t addr, uint32_t r0, uint32_t r1, uint32_t r2, uint32_t r3) {
    asm volatile("stmatrix.sync.aligned.m8n8.x4.shared.b16 [%0], {%1, %2, %3, %4};" ::"r"(addr), "r"(r0), "r"(r1), "r"(r2), "r"(r3) : "memory");
}
__device__ __forceinline__ void ldsm_x4(uint32_t addr, uint32_t& r0, uint32_t& r1, uint32_t& r2, uint32_t& r3) {
    asm volatile("ldmatrix.sync.aligned.m8n8.x4.shared.b16 {%0, %1, %2, %3}, [%4];" : "=r"(r0), "=r"(r1), "=r"(r2), "=r"(r3) : "r"(addr) : "memory");
}
__device__ __forceinline__ float nanmax(float a, float b) {
    float r;
    asm("max.NaN.f32 %0, %1, %2;" : "=f"(r) : "f"(a), "f"(b));
    return r;
}
__device__ __forceinline__ float ex2(float x) {
    float y;
    asm("ex2.approx.ftz.f32 %0, %1;" : "=f"(y) : "f"(x));
    return y;
}
__device__ __forceinline__ uint32_t wait_ge(const uint32_t* p, uint32_t target) {
    uint32_t v;
    asm volatile(
        "{\n"
        ".reg .pred q;\n"
        ".reg .u32 n;\n"
        ".reg .s32 d;\n"
        "mov.u32 n, 0;\n"
        "SPIN:\n"
        "ld.acquire.gpu.global.u32 %0, [%1];\n"
        "sub.s32 d, %0, %2;\n"
        "setp.ge.s32 q, d, 0;\n"
        "@q bra SPUN;\n"
        "nanosleep.u32 40;\n"
        "add.u32 n, n, 1;\n"
        "setp.lt.u32 q, n, 4000000;\n"
        "@q bra SPIN;\n"
        "trap;\n"
        "SPUN:\n"
        "}\n" : "=r"(v) : "l"(p), "r"(target) : "memory");
    return v;
}
__device__ __forceinline__ void fence_async_global() { asm volatile("fence.proxy.async.global;" ::: "memory"); }
__device__ __forceinline__ void signal_add(uint32_t* p) {
    asm volatile("{\n.reg .pred p;\nelect.sync _|p, 0xffffffff;\n@p fence.acq_rel.gpu;\n@p red.relaxed.gpu.global.add.u32 [%0], 1;\n}" ::"l"(p) : "memory");
}
__device__ __forceinline__ uint32_t signal_add_ret(uint32_t* p) {
    uint32_t v = 0;
    asm volatile("{\n.reg .pred p;\n.reg .u32 l;\nmov.u32 l, %%laneid;\nsetp.eq.u32 p, l, 0;\n@p fence.acq_rel.gpu;\n@p atom.relaxed.gpu.global.add.u32 %0, [%1], 1;\n}"
                 : "+r"(v) : "l"(p) : "memory");
    return __shfl_sync(0xffffffffu, v, 0);
}
__device__ __forceinline__ void tma_store_l0(const CUtensorMap* m, uint32_t src, int c0, int c1) {
    asm volatile("{\n.reg .pred p;\nelect.sync _|p, 0xffffffff;\n"
                 "@p cp.async.bulk.tensor.2d.global.shared::cta.bulk_group [%0, {%2, %3}], [%1];\n"
                 "@p cp.async.bulk.commit_group;\n}" ::"l"(m), "r"(src), "r"(c0), "r"(c1) : "memory");
}
__device__ __forceinline__ void bulk_reduce_f32_l0(void* dst, uint32_t src, uint32_t bytes) {
    asm volatile("{\n.reg .pred p;\nelect.sync _|p, 0xffffffff;\n"
                 "@p cp.reduce.async.bulk.global.shared::cta.bulk_group.add.f32 [%0], [%1], %2;\n"
                 "@p cp.async.bulk.commit_group;\n}" ::"l"(dst), "r"(src), "r"(bytes) : "memory");
}
__device__ __forceinline__ void publish_store(uint32_t* p) {
    asm volatile("{\n.reg .pred p;\nelect.sync _|p, 0xffffffff;\n@p cp.async.bulk.wait_group 0;\n"
                 "@p fence.proxy.async.global;\n@p red.relaxed.gpu.global.add.u32 [%0], 1;\n}" ::"l"(p) : "memory");
}
__device__ __forceinline__ float ldcg_f(const float* p) { float v; asm volatile("ld.global.cg.f32 %0, [%1];" : "=f"(v) : "l"(p) : "memory"); return v; }
__device__ __forceinline__ uint4 ldcg_u4(const void* p) {
    uint4 v;
    asm volatile("ld.global.cg.v4.b32 {%0, %1, %2, %3}, [%4];" : "=r"(v.x), "=r"(v.y), "=r"(v.z), "=r"(v.w) : "l"(p) : "memory");
    return v;
}
__device__ __forceinline__ void sts_u4(uint32_t a, uint32_t x, uint32_t y, uint32_t z, uint32_t w) {
    asm volatile("st.shared.v4.b32 [%0], {%1, %2, %3, %4};" ::"r"(a), "r"(x), "r"(y), "r"(z), "r"(w) : "memory");
}
__device__ __forceinline__ uint4 lds_u4(uint32_t a) {
    uint4 v;
    asm volatile("ld.shared.v4.b32 {%0, %1, %2, %3}, [%4];" : "=r"(v.x), "=r"(v.y), "=r"(v.z), "=r"(v.w) : "r"(a) : "memory");
    return v;
}

struct TrueT { static constexpr bool value = true; };
struct FalseT { static constexpr bool value = false; };

__device__ __forceinline__ void wg_ss128_z(float* d, uint32_t da, uint32_t db) {
    asm volatile("{\n.reg .b64 da, db;\nmov.b64 da, {%64, 0x40000040};\nmov.b64 db, {%65, 0x40000040};\n"
        "wgmma.mma_async.sync.aligned.m64n128k16.f32.bf16.bf16 {%0, %1, %2, %3, %4, %5, %6, %7, %8, %9, %10, %11, %12, %13, %14, %15, %16, %17, %18, %19, %20, %21, %22, %23, %24, %25, %26, %27, %28, %29, %30, %31, %32, %33, %34, %35, %36, %37, %38, %39, %40, %41, %42, %43, %44, %45, %46, %47, %48, %49, %50, %51, %52, %53, %54, %55, %56, %57, %58, %59, %60, %61, %62, %63}, da, db, 0, 1, 1, 0, 1;\n}"
        : "=f"(d[0]), "=f"(d[1]), "=f"(d[2]), "=f"(d[3]), "=f"(d[4]), "=f"(d[5]), "=f"(d[6]), "=f"(d[7]), "=f"(d[8]), "=f"(d[9]), "=f"(d[10]), "=f"(d[11]), "=f"(d[12]), "=f"(d[13]), "=f"(d[14]), "=f"(d[15]), "=f"(d[16]), "=f"(d[17]), "=f"(d[18]), "=f"(d[19]), "=f"(d[20]), "=f"(d[21]), "=f"(d[22]), "=f"(d[23]), "=f"(d[24]), "=f"(d[25]), "=f"(d[26]), "=f"(d[27]), "=f"(d[28]), "=f"(d[29]), "=f"(d[30]), "=f"(d[31]), "=f"(d[32]), "=f"(d[33]), "=f"(d[34]), "=f"(d[35]), "=f"(d[36]), "=f"(d[37]), "=f"(d[38]), "=f"(d[39]), "=f"(d[40]), "=f"(d[41]), "=f"(d[42]), "=f"(d[43]), "=f"(d[44]), "=f"(d[45]), "=f"(d[46]), "=f"(d[47]), "=f"(d[48]), "=f"(d[49]), "=f"(d[50]), "=f"(d[51]), "=f"(d[52]), "=f"(d[53]), "=f"(d[54]), "=f"(d[55]), "=f"(d[56]), "=f"(d[57]), "=f"(d[58]), "=f"(d[59]), "=f"(d[60]), "=f"(d[61]), "=f"(d[62]), "=f"(d[63]) : "r"(da), "r"(db));
}
__device__ __forceinline__ void wg_ss128(float* d, uint32_t da, uint32_t db) {
    asm volatile("{\n.reg .b64 da, db;\nmov.b64 da, {%64, 0x40000040};\nmov.b64 db, {%65, 0x40000040};\n"
        "wgmma.mma_async.sync.aligned.m64n128k16.f32.bf16.bf16 {%0, %1, %2, %3, %4, %5, %6, %7, %8, %9, %10, %11, %12, %13, %14, %15, %16, %17, %18, %19, %20, %21, %22, %23, %24, %25, %26, %27, %28, %29, %30, %31, %32, %33, %34, %35, %36, %37, %38, %39, %40, %41, %42, %43, %44, %45, %46, %47, %48, %49, %50, %51, %52, %53, %54, %55, %56, %57, %58, %59, %60, %61, %62, %63}, da, db, 1, 1, 1, 0, 1;\n}"
        : "+f"(d[0]), "+f"(d[1]), "+f"(d[2]), "+f"(d[3]), "+f"(d[4]), "+f"(d[5]), "+f"(d[6]), "+f"(d[7]), "+f"(d[8]), "+f"(d[9]), "+f"(d[10]), "+f"(d[11]), "+f"(d[12]), "+f"(d[13]), "+f"(d[14]), "+f"(d[15]), "+f"(d[16]), "+f"(d[17]), "+f"(d[18]), "+f"(d[19]), "+f"(d[20]), "+f"(d[21]), "+f"(d[22]), "+f"(d[23]), "+f"(d[24]), "+f"(d[25]), "+f"(d[26]), "+f"(d[27]), "+f"(d[28]), "+f"(d[29]), "+f"(d[30]), "+f"(d[31]), "+f"(d[32]), "+f"(d[33]), "+f"(d[34]), "+f"(d[35]), "+f"(d[36]), "+f"(d[37]), "+f"(d[38]), "+f"(d[39]), "+f"(d[40]), "+f"(d[41]), "+f"(d[42]), "+f"(d[43]), "+f"(d[44]), "+f"(d[45]), "+f"(d[46]), "+f"(d[47]), "+f"(d[48]), "+f"(d[49]), "+f"(d[50]), "+f"(d[51]), "+f"(d[52]), "+f"(d[53]), "+f"(d[54]), "+f"(d[55]), "+f"(d[56]), "+f"(d[57]), "+f"(d[58]), "+f"(d[59]), "+f"(d[60]), "+f"(d[61]), "+f"(d[62]), "+f"(d[63]) : "r"(da), "r"(db));
}
__device__ __forceinline__ void wg_ss192_z(float* d, uint32_t da, uint32_t db) {
    asm volatile("{\n.reg .b64 da, db;\nmov.b64 da, {%96, 0x40000040};\nmov.b64 db, {%97, 0x40000040};\n"
        "wgmma.mma_async.sync.aligned.m64n192k16.f32.bf16.bf16 {%0, %1, %2, %3, %4, %5, %6, %7, %8, %9, %10, %11, %12, %13, %14, %15, %16, %17, %18, %19, %20, %21, %22, %23, %24, %25, %26, %27, %28, %29, %30, %31, %32, %33, %34, %35, %36, %37, %38, %39, %40, %41, %42, %43, %44, %45, %46, %47, %48, %49, %50, %51, %52, %53, %54, %55, %56, %57, %58, %59, %60, %61, %62, %63, %64, %65, %66, %67, %68, %69, %70, %71, %72, %73, %74, %75, %76, %77, %78, %79, %80, %81, %82, %83, %84, %85, %86, %87, %88, %89, %90, %91, %92, %93, %94, %95}, da, db, 0, 1, 1, 0, 1;\n}"
        : "=f"(d[0]), "=f"(d[1]), "=f"(d[2]), "=f"(d[3]), "=f"(d[4]), "=f"(d[5]), "=f"(d[6]), "=f"(d[7]), "=f"(d[8]), "=f"(d[9]), "=f"(d[10]), "=f"(d[11]), "=f"(d[12]), "=f"(d[13]), "=f"(d[14]), "=f"(d[15]), "=f"(d[16]), "=f"(d[17]), "=f"(d[18]), "=f"(d[19]), "=f"(d[20]), "=f"(d[21]), "=f"(d[22]), "=f"(d[23]), "=f"(d[24]), "=f"(d[25]), "=f"(d[26]), "=f"(d[27]), "=f"(d[28]), "=f"(d[29]), "=f"(d[30]), "=f"(d[31]), "=f"(d[32]), "=f"(d[33]), "=f"(d[34]), "=f"(d[35]), "=f"(d[36]), "=f"(d[37]), "=f"(d[38]), "=f"(d[39]), "=f"(d[40]), "=f"(d[41]), "=f"(d[42]), "=f"(d[43]), "=f"(d[44]), "=f"(d[45]), "=f"(d[46]), "=f"(d[47]), "=f"(d[48]), "=f"(d[49]), "=f"(d[50]), "=f"(d[51]), "=f"(d[52]), "=f"(d[53]), "=f"(d[54]), "=f"(d[55]), "=f"(d[56]), "=f"(d[57]), "=f"(d[58]), "=f"(d[59]), "=f"(d[60]), "=f"(d[61]), "=f"(d[62]), "=f"(d[63]), "=f"(d[64]), "=f"(d[65]), "=f"(d[66]), "=f"(d[67]), "=f"(d[68]), "=f"(d[69]), "=f"(d[70]), "=f"(d[71]), "=f"(d[72]), "=f"(d[73]), "=f"(d[74]), "=f"(d[75]), "=f"(d[76]), "=f"(d[77]), "=f"(d[78]), "=f"(d[79]), "=f"(d[80]), "=f"(d[81]), "=f"(d[82]), "=f"(d[83]), "=f"(d[84]), "=f"(d[85]), "=f"(d[86]), "=f"(d[87]), "=f"(d[88]), "=f"(d[89]), "=f"(d[90]), "=f"(d[91]), "=f"(d[92]), "=f"(d[93]), "=f"(d[94]), "=f"(d[95]) : "r"(da), "r"(db));
}
__device__ __forceinline__ void wg_ss192(float* d, uint32_t da, uint32_t db) {
    asm volatile("{\n.reg .b64 da, db;\nmov.b64 da, {%96, 0x40000040};\nmov.b64 db, {%97, 0x40000040};\n"
        "wgmma.mma_async.sync.aligned.m64n192k16.f32.bf16.bf16 {%0, %1, %2, %3, %4, %5, %6, %7, %8, %9, %10, %11, %12, %13, %14, %15, %16, %17, %18, %19, %20, %21, %22, %23, %24, %25, %26, %27, %28, %29, %30, %31, %32, %33, %34, %35, %36, %37, %38, %39, %40, %41, %42, %43, %44, %45, %46, %47, %48, %49, %50, %51, %52, %53, %54, %55, %56, %57, %58, %59, %60, %61, %62, %63, %64, %65, %66, %67, %68, %69, %70, %71, %72, %73, %74, %75, %76, %77, %78, %79, %80, %81, %82, %83, %84, %85, %86, %87, %88, %89, %90, %91, %92, %93, %94, %95}, da, db, 1, 1, 1, 0, 1;\n}"
        : "+f"(d[0]), "+f"(d[1]), "+f"(d[2]), "+f"(d[3]), "+f"(d[4]), "+f"(d[5]), "+f"(d[6]), "+f"(d[7]), "+f"(d[8]), "+f"(d[9]), "+f"(d[10]), "+f"(d[11]), "+f"(d[12]), "+f"(d[13]), "+f"(d[14]), "+f"(d[15]), "+f"(d[16]), "+f"(d[17]), "+f"(d[18]), "+f"(d[19]), "+f"(d[20]), "+f"(d[21]), "+f"(d[22]), "+f"(d[23]), "+f"(d[24]), "+f"(d[25]), "+f"(d[26]), "+f"(d[27]), "+f"(d[28]), "+f"(d[29]), "+f"(d[30]), "+f"(d[31]), "+f"(d[32]), "+f"(d[33]), "+f"(d[34]), "+f"(d[35]), "+f"(d[36]), "+f"(d[37]), "+f"(d[38]), "+f"(d[39]), "+f"(d[40]), "+f"(d[41]), "+f"(d[42]), "+f"(d[43]), "+f"(d[44]), "+f"(d[45]), "+f"(d[46]), "+f"(d[47]), "+f"(d[48]), "+f"(d[49]), "+f"(d[50]), "+f"(d[51]), "+f"(d[52]), "+f"(d[53]), "+f"(d[54]), "+f"(d[55]), "+f"(d[56]), "+f"(d[57]), "+f"(d[58]), "+f"(d[59]), "+f"(d[60]), "+f"(d[61]), "+f"(d[62]), "+f"(d[63]), "+f"(d[64]), "+f"(d[65]), "+f"(d[66]), "+f"(d[67]), "+f"(d[68]), "+f"(d[69]), "+f"(d[70]), "+f"(d[71]), "+f"(d[72]), "+f"(d[73]), "+f"(d[74]), "+f"(d[75]), "+f"(d[76]), "+f"(d[77]), "+f"(d[78]), "+f"(d[79]), "+f"(d[80]), "+f"(d[81]), "+f"(d[82]), "+f"(d[83]), "+f"(d[84]), "+f"(d[85]), "+f"(d[86]), "+f"(d[87]), "+f"(d[88]), "+f"(d[89]), "+f"(d[90]), "+f"(d[91]), "+f"(d[92]), "+f"(d[93]), "+f"(d[94]), "+f"(d[95]) : "r"(da), "r"(db));
}
__device__ __forceinline__ void wg_qk_z(float* d, uint32_t a0, uint32_t a1, uint32_t a2, uint32_t a3, uint64_t db) {
    asm volatile("wgmma.mma_async.sync.aligned.m64n64k16.f32.bf16.bf16 {%0, %1, %2, %3, %4, %5, %6, %7, %8, %9, %10, %11, %12, %13, %14, %15, %16, %17, %18, %19, %20, %21, %22, %23, %24, %25, %26, %27, %28, %29, %30, %31}, {%32, %33, %34, %35}, %36, 0, 1, 1, 0;"
        : "=f"(d[0]), "=f"(d[1]), "=f"(d[2]), "=f"(d[3]), "=f"(d[4]), "=f"(d[5]), "=f"(d[6]), "=f"(d[7]), "=f"(d[8]), "=f"(d[9]), "=f"(d[10]), "=f"(d[11]), "=f"(d[12]), "=f"(d[13]), "=f"(d[14]), "=f"(d[15]), "=f"(d[16]), "=f"(d[17]), "=f"(d[18]), "=f"(d[19]), "=f"(d[20]), "=f"(d[21]), "=f"(d[22]), "=f"(d[23]), "=f"(d[24]), "=f"(d[25]), "=f"(d[26]), "=f"(d[27]), "=f"(d[28]), "=f"(d[29]), "=f"(d[30]), "=f"(d[31]) : "r"(a0), "r"(a1), "r"(a2), "r"(a3), "l"(db));
}
__device__ __forceinline__ void wg_qk(float* d, uint32_t a0, uint32_t a1, uint32_t a2, uint32_t a3, uint64_t db) {
    asm volatile("wgmma.mma_async.sync.aligned.m64n64k16.f32.bf16.bf16 {%0, %1, %2, %3, %4, %5, %6, %7, %8, %9, %10, %11, %12, %13, %14, %15, %16, %17, %18, %19, %20, %21, %22, %23, %24, %25, %26, %27, %28, %29, %30, %31}, {%32, %33, %34, %35}, %36, 1, 1, 1, 0;"
        : "+f"(d[0]), "+f"(d[1]), "+f"(d[2]), "+f"(d[3]), "+f"(d[4]), "+f"(d[5]), "+f"(d[6]), "+f"(d[7]), "+f"(d[8]), "+f"(d[9]), "+f"(d[10]), "+f"(d[11]), "+f"(d[12]), "+f"(d[13]), "+f"(d[14]), "+f"(d[15]), "+f"(d[16]), "+f"(d[17]), "+f"(d[18]), "+f"(d[19]), "+f"(d[20]), "+f"(d[21]), "+f"(d[22]), "+f"(d[23]), "+f"(d[24]), "+f"(d[25]), "+f"(d[26]), "+f"(d[27]), "+f"(d[28]), "+f"(d[29]), "+f"(d[30]), "+f"(d[31]) : "r"(a0), "r"(a1), "r"(a2), "r"(a3), "l"(db));
}
__device__ __forceinline__ void wg_pv(float* d, uint32_t a0, uint32_t a1, uint32_t a2, uint32_t a3, uint64_t db) {
    asm volatile("wgmma.mma_async.sync.aligned.m64n40k16.f32.bf16.bf16 {%0, %1, %2, %3, %4, %5, %6, %7, %8, %9, %10, %11, %12, %13, %14, %15, %16, %17, %18, %19}, {%20, %21, %22, %23}, %24, 1, 1, 1, 1;"
        : "+f"(d[0]), "+f"(d[1]), "+f"(d[2]), "+f"(d[3]), "+f"(d[4]), "+f"(d[5]), "+f"(d[6]), "+f"(d[7]), "+f"(d[8]), "+f"(d[9]), "+f"(d[10]), "+f"(d[11]), "+f"(d[12]), "+f"(d[13]), "+f"(d[14]), "+f"(d[15]), "+f"(d[16]), "+f"(d[17]), "+f"(d[18]), "+f"(d[19]) : "r"(a0), "r"(a1), "r"(a2), "r"(a3), "l"(db));
}
__device__ __forceinline__ void wg_rs40t(float* d, uint32_t a0, uint32_t a1, uint32_t a2, uint32_t a3, uint32_t db) {
    asm volatile("{\n.reg .b64 db;\nmov.b64 db, {%24, 0x80000020};\n"
        "wgmma.mma_async.sync.aligned.m64n40k16.f32.bf16.bf16 {%0, %1, %2, %3, %4, %5, %6, %7, %8, %9, %10, %11, %12, %13, %14, %15, %16, %17, %18, %19}, {%20, %21, %22, %23}, db, 1, 1, 1, 1;\n}"
        : "+f"(d[0]), "+f"(d[1]), "+f"(d[2]), "+f"(d[3]), "+f"(d[4]), "+f"(d[5]), "+f"(d[6]), "+f"(d[7]), "+f"(d[8]), "+f"(d[9]), "+f"(d[10]), "+f"(d[11]), "+f"(d[12]), "+f"(d[13]), "+f"(d[14]), "+f"(d[15]), "+f"(d[16]), "+f"(d[17]), "+f"(d[18]), "+f"(d[19]) : "r"(a0), "r"(a1), "r"(a2), "r"(a3), "r"(db));
}
__device__ __forceinline__ void wg_rs40t_z(float* d, uint32_t a0, uint32_t a1, uint32_t a2, uint32_t a3, uint32_t db) {
    asm volatile("{\n.reg .b64 db;\nmov.b64 db, {%24, 0x80000020};\n"
        "wgmma.mma_async.sync.aligned.m64n40k16.f32.bf16.bf16 {%0, %1, %2, %3, %4, %5, %6, %7, %8, %9, %10, %11, %12, %13, %14, %15, %16, %17, %18, %19}, {%20, %21, %22, %23}, db, 0, 1, 1, 1;\n}"
        : "=f"(d[0]), "=f"(d[1]), "=f"(d[2]), "=f"(d[3]), "=f"(d[4]), "=f"(d[5]), "=f"(d[6]), "=f"(d[7]), "=f"(d[8]), "=f"(d[9]), "=f"(d[10]), "=f"(d[11]), "=f"(d[12]), "=f"(d[13]), "=f"(d[14]), "=f"(d[15]), "=f"(d[16]), "=f"(d[17]), "=f"(d[18]), "=f"(d[19]) : "r"(a0), "r"(a1), "r"(a2), "r"(a3), "r"(db));
}
__device__ __forceinline__ void wg_rs32t_z(float* d, uint32_t a0, uint32_t a1, uint32_t a2, uint32_t a3, uint32_t db) {
    asm volatile("{\n.reg .b64 db;\nmov.b64 db, {%20, 0x80000020};\n"
        "wgmma.mma_async.sync.aligned.m64n32k16.f32.bf16.bf16 {%0, %1, %2, %3, %4, %5, %6, %7, %8, %9, %10, %11, %12, %13, %14, %15}, {%16, %17, %18, %19}, db, 0, 1, 1, 1;\n}"
        : "=f"(d[0]), "=f"(d[1]), "=f"(d[2]), "=f"(d[3]), "=f"(d[4]), "=f"(d[5]), "=f"(d[6]), "=f"(d[7]), "=f"(d[8]), "=f"(d[9]), "=f"(d[10]), "=f"(d[11]), "=f"(d[12]), "=f"(d[13]), "=f"(d[14]), "=f"(d[15]) : "r"(a0), "r"(a1), "r"(a2), "r"(a3), "r"(db));
}
__device__ __forceinline__ void wg_rs32t(float* d, uint32_t a0, uint32_t a1, uint32_t a2, uint32_t a3, uint32_t db) {
    asm volatile("{\n.reg .b64 db;\nmov.b64 db, {%20, 0x80000020};\n"
        "wgmma.mma_async.sync.aligned.m64n32k16.f32.bf16.bf16 {%0, %1, %2, %3, %4, %5, %6, %7, %8, %9, %10, %11, %12, %13, %14, %15}, {%16, %17, %18, %19}, db, 1, 1, 1, 1;\n}"
        : "+f"(d[0]), "+f"(d[1]), "+f"(d[2]), "+f"(d[3]), "+f"(d[4]), "+f"(d[5]), "+f"(d[6]), "+f"(d[7]), "+f"(d[8]), "+f"(d[9]), "+f"(d[10]), "+f"(d[11]), "+f"(d[12]), "+f"(d[13]), "+f"(d[14]), "+f"(d[15]) : "r"(a0), "r"(a1), "r"(a2), "r"(a3), "r"(db));
}
__device__ __forceinline__ void wg_ss40tt(float* d, uint32_t da, uint32_t db) {
    asm volatile("{\n.reg .b64 da, db;\nmov.b64 da, {%20, 0x40000040};\nmov.b64 db, {%21, 0x80000020};\n"
        "wgmma.mma_async.sync.aligned.m64n40k16.f32.bf16.bf16 {%0, %1, %2, %3, %4, %5, %6, %7, %8, %9, %10, %11, %12, %13, %14, %15, %16, %17, %18, %19}, da, db, 1, 1, 1, 1, 1;\n}"
        : "+f"(d[0]), "+f"(d[1]), "+f"(d[2]), "+f"(d[3]), "+f"(d[4]), "+f"(d[5]), "+f"(d[6]), "+f"(d[7]), "+f"(d[8]), "+f"(d[9]), "+f"(d[10]), "+f"(d[11]), "+f"(d[12]), "+f"(d[13]), "+f"(d[14]), "+f"(d[15]), "+f"(d[16]), "+f"(d[17]), "+f"(d[18]), "+f"(d[19]) : "r"(da), "r"(db));
}


constexpr int KVST = 2;
constexpr int KV_STAGE = 32768;
constexpr int OFF_KV = 0;
constexpr int OFF_Q = KVST * KV_STAGE;
constexpr int OFF_ONES = OFF_Q + 8192;
constexpr int MST = 3;
constexpr int M_STAGE = 40960;
constexpr int OFF_MM = OFF_ONES + 1024;
constexpr int OFF_PHI = OFF_MM + MST * M_STAGE;
constexpr int OFF_STG = OFF_PHI + 4096;
constexpr int OFF_ASTG = OFF_STG + 8 * 2048;
constexpr int OFF_BAR = OFF_ASTG + 8 * 1024;
constexpr int SMEM_BYTES = OFF_BAR + 256 + 1024;
static_assert(OFF_MM % 1024 == 0 && OFF_PHI % 1024 == 0 && OFF_STG % 1024 == 0, "alignment");
constexpr int B_KVFULL = OFF_BAR, B_QFULL = B_KVFULL + 8 * KVST, B_MFULL = B_QFULL + 8, B_PHI = B_MFULL + 8 * MST;
constexpr int OST = 4;
constexpr int O_STAGE = 32768;
constexpr int B_OFULL = B_PHI + 8;
constexpr int C_KV = B_OFULL + 8 * OST, C_MM = C_KV + 4 * KVST, C_OUT = C_MM + 4 * MST, OFF_FAST = C_OUT + 4 * OST;
static_assert(OFF_FAST + 4 <= OFF_BAR + 256, "barrier area");
static_assert(OFF_MM + OST * O_STAGE <= OFF_STG + 4096, "output ring overlaps its staging");

constexpr float QSCALE = 0.17677669529663687f * 1.4426950408889634f;
constexpr float SAFE_BOUND = 90.0f;

constexpr int QKV_BATCH = 2, OUT_BATCH = 4;
constexpr int FAST_KSTEPS = 5;

__device__ __forceinline__ void exp_pack8(const float* s, uint32_t* p) {
#pragma unroll
    for (int i = 0; i < 4; i++) p[i] = pack_bf16(ex2(s[2 * i]), ex2(s[2 * i + 1]));
}

__device__ __forceinline__ float rcp_approx(float x) { float y; asm("rcp.approx.ftz.f32 %0, %1;" : "=f"(y) : "f"(x)); return y; }
__device__ __forceinline__ uint32_t softmax_is_safe(int h, int lane) {
    float qm = 0.f, km = 0.f, vm = 0.f;
#pragma unroll
    for (int i = 0; i < 4; i++) {
        qm = nanmax(qm, ldcg_f(&g_norm[(0 * NH + h) * 128 + lane + 32 * i]));
        km = nanmax(km, ldcg_f(&g_norm[(1 * NH + h) * 128 + lane + 32 * i]));
        vm = nanmax(vm, ldcg_f(&g_norm[(2 * NH + h) * 128 + lane + 32 * i]));
    }
    qm = __uint_as_float(__reduce_max_sync(0xffffffffu, __float_as_uint(qm) & 0x7fffffffu));
    km = __uint_as_float(__reduce_max_sync(0xffffffffu, __float_as_uint(km) & 0x7fffffffu));
    vm = __uint_as_float(__reduce_max_sync(0xffffffffu, __float_as_uint(vm) & 0x7fffffffu));
    return (qm * km * 1.05f <= SAFE_BOUND * SAFE_BOUND) && (qm < 1e30f) && (km < 1e30f) && (vm >= 0.0009765625f) && (vm <= 1048576.f);
}

__device__ __forceinline__ void publish_b_tile(const int nt, const uint32_t ep1) {
    const uint32_t old = signal_add_ret(&g_sync.cntB[nt * CS]);
    if (old == ep1 * 32 - 1) {
        const int lane = threadIdx.x & 31;
#pragma unroll
        for (int hh = 0; hh < 2; hh++) {
            const uint32_t okf = softmax_is_safe(nt * 2 + hh, lane);
            if (lane == 0) asm volatile("st.relaxed.gpu.global.u32 [%0], %1;" ::"l"(&g_sync.flagB[(nt * 2 + hh) * CS]), "r"((ep1 << 1) | okf) : "memory");
        }
    }
}

__device__ __forceinline__ int task_h(int t) { return t >> 4; }
__device__ __forceinline__ int task_q(int t) { return t & 15; }

__device__ __forceinline__ bool release_slot(uint32_t ctr) {
    uint32_t old = 0;
    asm volatile("{\n.reg .pred p;\nelect.sync _|p, 0xffffffff;\n@p atom.relaxed.cta.shared.inc.u32 %0, [%1], 7;\n}" : "+r"(old) : "r"(ctr) : "memory");
    return __reduce_max_sync(0xffffffffu, old) == 7;
}

__device__ __forceinline__ void att_role(const TMaps& tm, const uint32_t sb, const int wg, const int warp, const uint32_t ep1) {
    constexpr int NTASK = NH * 16;
    auto load_stage = [&](int t, int st, bool ahead) {
        const int h = task_h(t), qt = task_q(t), slot = st & (KVST - 1);
        if (ahead) {
            const uint32_t fl = wait_ge(&g_sync.flagB[h * CS], ep1 << 1);
            fence_async_global();
            if (st == 0) {
                asm volatile("st.shared.u32 [%0], %1;" ::"r"(sb + OFF_FAST), "r"(fl & 1u) : "memory");
                mbar_expect_tx_l0(sb + B_QFULL, 8192);
                bulk_load_l0(sb + OFF_Q, g_qkv + ((size_t)((3 + 0) * NH + h) * SEQ + qt * 128) * 32, 8192, sb + B_QFULL);
            }
        }
        const uint32_t dst = sb + OFF_KV + slot * KV_STAGE, fb = sb + B_KVFULL + 8 * slot;
        mbar_expect_tx_l0(fb, KV_STAGE);
        bulk_load_l0(dst, g_qkv + ((size_t)((3 + 1) * NH + h) * SEQ + st * 256) * 32, 16384, fb);
        bulk_load_l0(dst + 16384, g_qkv + ((size_t)((3 + 2) * NH + h) * SEQ + st * 256) * 32, 16384, fb);
    };
    auto refill = [&](int t, int st, bool acq) {
        const int ns = st + KVST;
        if (ns < 8) load_stage(t, ns, false);
        else if (t + (int)gridDim.x < NTASK) load_stage(t + gridDim.x, ns - 8, acq);
    };
    bar_sync(13 + wg, 256);
    if (warp == 1) publish_b_tile(blockIdx.x >> 4, ep1);
    if (wg == 0 && warp == 0 && (int)blockIdx.x < NTASK) {
        const int t = blockIdx.x, h = task_h(t), qt = task_q(t);
        wait_ge(&g_sync.cntB[(h >> 1) * CS], ep1 * 32);
        fence_async_global();
        mbar_expect_tx_noarrive_l0(sb + B_QFULL, 8192);
        bulk_load_l0(sb + OFF_Q, g_qkv + ((size_t)((3 + 0) * NH + h) * SEQ + qt * 128) * 32, 8192, sb + B_QFULL);
#pragma unroll 1
        for (int i = 0; i < KVST; i++) load_stage(t, i, false);
        const uint32_t okf = softmax_is_safe(h, threadIdx.x & 31);
        asm volatile("st.shared.u32 [%0], %1;" ::"r"(sb + OFF_FAST), "r"(okf) : "memory");
        mbar_arrive_lane0(sb + B_QFULL);
    }

    uint32_t ph = 0, qph = 0;
    constexpr uint64_t DV_STEP = (uint64_t)(int64_t)(64 - (64 << 16));
    constexpr uint64_t V_STAGE_STEP = (uint64_t)(int64_t)(2048 - (2048 << 16));
    const uint64_t k_lo0 = (0x80000020ull << 32) | desc_lo(sb + OFF_KV, 16);
    const uint64_t v_lo0 = (0x80000020ull << 32) | desc_lo(sb + OFF_KV + 16384, OFF_ONES - OFF_KV - 16384);
    int pend = -1;
    uint32_t q[8];
    float s0[32];
    auto load_q = [&]() -> int {
        mbar_wait(sb + B_QFULL, qph);
        qph ^= 1;
        uint32_t tidl;
        asm volatile("mov.u32 %0, %%tid.x;" : "=r"(tidl));
        const int lane = tidl & 31;
        const int qrow = wg * 64 + warp * 16 + (lane & 7) + ((lane >> 3) & 1) * 8;
        const uint32_t qa = sb + OFF_Q + qrow * 64;
        const uint32_t x = (qrow >> 1) & 3, c = lane >> 4;
        ldsm_x4(qa + (((0 + c) ^ x) << 4), q[0], q[1], q[2], q[3]);
        ldsm_x4(qa + (((2 + c) ^ x) << 4), q[4], q[5], q[6], q[7]);
        uint32_t f;
        asm volatile("ld.shared.u32 %0, [%1];" : "=r"(f) : "r"(sb + OFF_FAST) : "memory");
        fence_regs_u<8>(q);
        return __shfl_sync(0xffffffffu, f, 0);
    };
    auto qk = [&](float* sc, uint64_t dK) {
        wg_fence();
        wg_qk_z(sc, q[0], q[1], q[2], q[3], dK);
        wg_qk(sc, q[4], q[5], q[6], q[7], dK + 2);
        wg_commit();
    };
    auto start_task = [&]() -> int {
        const int f = load_q();
        mbar_wait(sb + B_KVFULL, ph);
        qk(s0, k_lo0);
        wg_wait<0>();
        fence_regs<32>(s0);
        return f;
    };
    if ((int)blockIdx.x >= NTASK) return;
    int fast = start_task();
    for (int t = blockIdx.x; t < NTASK; t += gridDim.x) {
        const int h = task_h(t), qt = task_q(t);
        const bool has_next = t + (int)gridDim.x < NTASK;
        int fast_next = 0;
        float o[20];
#pragma unroll
        for (int i = 0; i < 20; i++) o[i] = 0.f;
        fence_regs<20>(o);

        if (fast) {
            float s1[32];
            uint32_t p0[16], p1[16];
            auto exp_pv = [&](const float* sc, uint32_t* p, uint64_t dV) {
#pragma unroll
                for (int kk = 0; kk < 4; kk++) {
                    exp_pack8(sc + 8 * kk, p + 4 * kk);
                    wg_fence();
                    wg_pv(o, p[4 * kk], p[4 * kk + 1], p[4 * kk + 2], p[4 * kk + 3], dV + kk * DV_STEP);
                }
                wg_commit();
            };
            auto half = [&](float* snext, uint64_t dKn, const float* scur, uint32_t* p, uint64_t dVc) {
                qk(snext, dKn);
                exp_pv(scur, p, dVc);
                wg_wait<1>();
                fence_regs<32>(snext);
            };
#pragma unroll 1
            for (int st = 0; st < 8; st++) {
                const int slot = st & 1;
                const uint64_t dK = k_lo0 + slot * 2048, dV = v_lo0 + slot * V_STAGE_STEP;
                half(s1, dK + 256, s0, p0, dV);
                if (st > 0) { if (__builtin_expect(release_slot(sb + C_KV + 4 * (slot ^ 1)), 0)) refill(t, st - 1, true); }
                if (__builtin_expect(st == 1 && pend >= 0, 0)) { publish_store(&g_sync.cntOB[pend * CS]); pend = -1; }
                half(s0, dK + 512, s1, p1, dV + 4 * DV_STEP);
                half(s1, dK + 768, s0, p0, dV + 8 * DV_STEP);
                if (slot) ph ^= 1;
                if (st < 7 || has_next) {
                    if (st == 7) fast_next = load_q();
                    mbar_wait(sb + B_KVFULL + 8 * (slot ^ 1), ph);
                }
                half(s0, k_lo0 + (slot ^ 1) * 2048, s1, p1, dV + 12 * DV_STEP);
            }
            wg_wait<0>();
            fence_regs<20>(o);
            if (release_slot(sb + C_KV + 4 * 1)) refill(t, 7, false);
        } else {
            float sc[32];
            uint32_t p[16];
            float m0 = -INFINITY, m1 = -INFINITY;
            if (pend >= 0) { publish_store(&g_sync.cntOB[pend * CS]); pend = -1; }
#pragma unroll 1
            for (int st = 0; st < 8; st++) {
                const int slot = st & (KVST - 1);
                mbar_wait(sb + B_KVFULL + 8 * slot, ph);
                const uint64_t dK = k_lo0 + slot * 2048, dV = v_lo0 + slot * V_STAGE_STEP;
#pragma unroll 1
                for (int sub = 0; sub < 4; sub++) {
                    wg_fence();
                    wg_qk_z(sc, q[0], q[1], q[2], q[3], dK + sub * 256);
                    wg_qk(sc, q[4], q[5], q[6], q[7], dK + sub * 256 + 2);
                    wg_commit();
                    wg_wait<0>();
                    fence_regs<32>(sc);
                    float x0 = m0, x1 = m1;
#pragma unroll
                    for (int j = 0; j < 8; j++) {
                        x0 = fmaxf(x0, fmaxf(sc[4 * j], sc[4 * j + 1]));
                        x1 = fmaxf(x1, fmaxf(sc[4 * j + 2], sc[4 * j + 3]));
                    }
                    x0 = fmaxf(x0, __shfl_xor_sync(0xffffffffu, x0, 1)); x0 = fmaxf(x0, __shfl_xor_sync(0xffffffffu, x0, 2));
                    x1 = fmaxf(x1, __shfl_xor_sync(0xffffffffu, x1, 1)); x1 = fmaxf(x1, __shfl_xor_sync(0xffffffffu, x1, 2));
                    const float al0 = ex2(m0 - x0), al1 = ex2(m1 - x1);
                    m0 = x0; m1 = x1;
#pragma unroll
                    for (int j = 0; j < 5; j++) { o[4 * j] *= al0; o[4 * j + 1] *= al0; o[4 * j + 2] *= al1; o[4 * j + 3] *= al1; }
#pragma unroll
                    for (int j = 0; j < 8; j++) {
                        p[2 * j] = pack_bf16(ex2(sc[4 * j] - x0), ex2(sc[4 * j + 1] - x0));
                        p[2 * j + 1] = pack_bf16(ex2(sc[4 * j + 2] - x1), ex2(sc[4 * j + 3] - x1));
                    }
                    fence_regs<20>(o); fence_regs_u<16>(p);
                    wg_fence();
#pragma unroll
                    for (int kk = 0; kk < 4; kk++) wg_pv(o, p[4 * kk], p[4 * kk + 1], p[4 * kk + 2], p[4 * kk + 3], dV + (sub * 4 + kk) * DV_STEP);
                    wg_commit();
                    wg_wait<0>();
                    fence_regs<20>(o);
                }
                if (release_slot(sb + C_KV + 4 * slot)) refill(t, st, true);
                if (slot == KVST - 1) ph ^= 1;
            }
            if (has_next) fast_next = start_task();
        }
        uint32_t tidl;
        asm volatile("mov.u32 %0, %%tid.x;" : "=r"(tidl));
        const int lane = tidl & 31;
        const float l0 = __shfl_sync(0xffffffffu, o[16], lane & ~3), l1 = __shfl_sync(0xffffffffu, o[18], lane & ~3);
        const float i0 = rcp_approx(l0), i1 = rcp_approx(l1);
        {
            const uint32_t stg = sb + OFF_ASTG + (wg * 4 + warp) * 1024;
            const int strow = (lane & 7) + ((lane >> 3) & 1) * 8;
            const uint32_t sa = stg + strow * 64, x = (strow >> 1) & 3, c = lane >> 4;
            stsm_x4(sa + ((c ^ x) << 4), pack_bf16(o[0] * i0, o[1] * i0), pack_bf16(o[2] * i1, o[3] * i1), pack_bf16(o[4] * i0, o[5] * i0), pack_bf16(o[6] * i1, o[7] * i1));
            stsm_x4(sa + (((2 + c) ^ x) << 4), pack_bf16(o[8] * i0, o[9] * i0), pack_bf16(o[10] * i1, o[11] * i1), pack_bf16(o[12] * i0, o[13] * i0), pack_bf16(o[14] * i1, o[15] * i1));
            fence_async_smem();
            __syncwarp();
            tma_store_l0(&tm.ost, stg, h * 32, SEQ + qt * 128 + wg * 64 + warp * 16);
        }
        pend = qt + (h >= 24 ? 16 : 0);
        fast = fast_next;
    }
    if (pend >= 0) publish_store(&g_sync.cntOB[pend * CS]);
}

template <int NR>
__device__ __forceinline__ void hedgehog_rows(const uint4* raw, uint32_t (*pos)[4], uint32_t (*neg)[4]) {
    constexpr float L2E = 1.4426950408889634f;
    float x[NR][8], mx[NR], mn[NR];
#pragma unroll
    for (int r = 0; r < NR; r++) {
        const uint32_t w[4] = {raw[r].x, raw[r].y, raw[r].z, raw[r].w};
#pragma unroll
        for (int i = 0; i < 4; i++) { x[r][2 * i] = __uint_as_float(w[i] << 16); x[r][2 * i + 1] = __uint_as_float(w[i] & 0xffff0000u); }
        mx[r] = fmaxf(fmaxf(fmaxf(x[r][0], x[r][1]), fmaxf(x[r][2], x[r][3])), fmaxf(fmaxf(x[r][4], x[r][5]), fmaxf(x[r][6], x[r][7])));
        mn[r] = fminf(fminf(fminf(x[r][0], x[r][1]), fminf(x[r][2], x[r][3])), fminf(fminf(x[r][4], x[r][5]), fminf(x[r][6], x[r][7])));
    }
#pragma unroll
    for (int o = 1; o < 4; o <<= 1) {
#pragma unroll
        for (int r = 0; r < NR; r++) {
            mx[r] = fmaxf(mx[r], __shfl_xor_sync(0xffffffffu, mx[r], o));
            mn[r] = fminf(mn[r], __shfl_xor_sync(0xffffffffu, mn[r], o));
        }
    }
    float ep[NR][8], en[NR][8], sp[NR], sn[NR];
#pragma unroll
    for (int r = 0; r < NR; r++) {
        const float mxs = -mx[r] * L2E, mns = mn[r] * L2E;
#pragma unroll
        for (int i = 0; i < 8; i++) {
            ep[r][i] = ex2(fmaf(x[r][i], L2E, mxs));
            en[r][i] = ex2(fmaf(x[r][i], -L2E, mns));
        }
        sp[r] = ((ep[r][0] + ep[r][1]) + (ep[r][2] + ep[r][3])) + ((ep[r][4] + ep[r][5]) + (ep[r][6] + ep[r][7]));
        sn[r] = ((en[r][0] + en[r][1]) + (en[r][2] + en[r][3])) + ((en[r][4] + en[r][5]) + (en[r][6] + en[r][7]));
    }
#pragma unroll
    for (int o = 1; o < 4; o <<= 1) {
#pragma unroll
        for (int r = 0; r < NR; r++) {
            sp[r] += __shfl_xor_sync(0xffffffffu, sp[r], o);
            sn[r] += __shfl_xor_sync(0xffffffffu, sn[r], o);
        }
    }
#pragma unroll
    for (int r = 0; r < NR; r++) {
        const float ip = rcp_approx(sp[r]), in = rcp_approx(sn[r]);
#pragma unroll
        for (int i = 0; i < 4; i++) {
            pos[r][i] = pack_bf16(ep[r][2 * i] * ip, ep[r][2 * i + 1] * ip);
            neg[r][i] = pack_bf16(en[r][2 * i] * in, en[r][2 * i + 1] * in);
        }
    }
}

struct Ring { int s; uint32_t ph; };

template <int BN> __device__ __forceinline__ void wg_mm_z(float* d, uint32_t a, uint32_t b);
template <> __device__ __forceinline__ void wg_mm_z<128>(float* d, uint32_t a, uint32_t b) { wg_ss128_z(d, a, b); }
template <> __device__ __forceinline__ void wg_mm_z<192>(float* d, uint32_t a, uint32_t b) { wg_ss192_z(d, a, b); }
template <int BN> __device__ __forceinline__ void wg_mm(float* d, uint32_t a, uint32_t b);
template <> __device__ __forceinline__ void wg_mm<128>(float* d, uint32_t a, uint32_t b) { wg_ss128(d, a, b); }
template <> __device__ __forceinline__ void wg_mm<192>(float* d, uint32_t a, uint32_t b) { wg_ss192(d, a, b); }

template <int N> struct IntT { static constexpr int value = N; };
template <int BN, bool POLITE, int PBATCH, int NST, int STAGE, int BFULL, int CTR, typename Refill, typename AtStep, typename Fast>
__device__ __forceinline__ void mm_tile(float* acc, const uint32_t sb, const int wgm, Ring& c, Refill&& refill, AtStep&& at_step, Fast&& full_speed) {
    int prev = 0;
    auto kstep = [&](auto first, int kt) {
        mbar_wait(sb + BFULL + 8 * c.s, c.ph);
        at_step(kt);
        const uint32_t st = sb + OFF_MM + c.s * STAGE;
        const uint32_t dA = desc_lo(st + wgm * 8192, 16);
        const uint32_t dB = desc_lo(st + 16384, 8192);
        if (POLITE) {
            auto run = [&](auto pb) {
                constexpr int PB = decltype(pb)::value;
#pragma unroll
                for (int kk = 0; kk < 4; kk++) {
                    if (kk % PB == 0) wg_fence();
                    if (decltype(first)::value && kk == 0) wg_mm_z<BN>(acc, dA + kk * 2, dB + kk * 128);
                    else wg_mm<BN>(acc, dA + kk * 2, dB + kk * 128);
                    if (kk % PB == PB - 1) { wg_commit(); wg_wait<0>(); }
                }
            };
            if (full_speed(kt)) run(IntT<4>{}); else run(IntT<PBATCH>{});
            if (__builtin_expect(release_slot(sb + CTR + 4 * c.s), 0)) refill(kt, c.s);
        } else {
            wg_fence();
#pragma unroll
            for (int kk = 0; kk < 4; kk++) {
                if (decltype(first)::value && kk == 0) wg_mm_z<BN>(acc, dA + kk * 2, dB + kk * 128);
                else wg_mm<BN>(acc, dA + kk * 2, dB + kk * 128);
            }
            wg_commit();
            if (!decltype(first)::value) {
                wg_wait<1>();
                if (__builtin_expect(release_slot(sb + CTR + 4 * prev), 0)) refill(kt - 1, prev);
            }
            prev = c.s;
        }
        if (++c.s == NST) { c.s = 0; c.ph ^= 1; }
    };
    kstep(TrueT{}, 0);
#pragma unroll 1
    for (int kt = 1; kt < 16; kt++) kstep(FalseT{}, kt);
    if (!POLITE) {
        wg_wait<0>();
        if (release_slot(sb + CTR + 4 * prev)) refill(15, prev);
    }
    fence_regs<BN / 2>(acc);
}

template <int HSTRIDE>
__device__ __forceinline__ void qkv_epilogue(float* a, const uint32_t sb, const uint32_t stg_base, const uint32_t stg_stride, const int prob, const int mt,
                                             const int nt, const int wgm, const int warp, const uint32_t ep1, const uint32_t phi_ph) {
    uint32_t tidl;
    asm volatile("mov.u32 %0, %%tid.x;" : "=r"(tidl));
    const int lane = tidl & 31;
    const uint32_t stg = stg_base + ((tidl >> 5) & 7) * stg_stride;
    const int strow = (lane & 7) + ((lane >> 3) & 1) * 8;
    const uint32_t st_base = stg + strow * 64;
    const uint32_t st_x = (strow >> 1) & 3, st_c = lane >> 4;
    const uint32_t ld_base = stg + (lane >> 2) * 64 + (((lane & 3) ^ ((lane >> 3) & 3)) << 4);
    const int tok0 = mt * 128 + wgm * 64 + warp * 16;
    auto stage_block = [&](int hh, const uint32_t* pk) {
        stsm_x4(st_base + hh * HSTRIDE + ((st_c ^ st_x) << 4), pk[0], pk[1], pk[2], pk[3]);
        stsm_x4(st_base + hh * HSTRIDE + (((2 + st_c) ^ st_x) << 4), pk[4], pk[5], pk[6], pk[7]);
    };
    auto flush = [&](int p) {
        __syncwarp();
#pragma unroll
        for (int hh = 0; hh < 2; hh++) {
            uint4* dst = reinterpret_cast<uint4*>(g_qkv + ((size_t)((prob * 3 + p) * NH + nt * 2 + hh) * SEQ + tok0) * 32) + lane;
            const uint32_t la = prob == 1 ? stg + lane * 16 : ld_base;
            const uint4 v0 = lds_u4(la + hh * HSTRIDE), v1 = lds_u4(la + hh * HSTRIDE + 512);
            dst[0] = v0; dst[32] = v1;
        }
        __syncwarp();
    };
    if (prob == 1) {
        float nrm[6];
#pragma unroll
        for (int p = 0; p < 3; p++) {
#pragma unroll
            for (int hh = 0; hh < 2; hh++) {
                float s0 = 0.f, s1 = 0.f;
                uint32_t pk[8];
#pragma unroll
                for (int g = 0; g < 4; g++) {
                    const int j = p * 8 + hh * 4 + g;
                    float v0 = a[4 * j], v1 = a[4 * j + 1], v2 = a[4 * j + 2], v3 = a[4 * j + 3];
                    if (p == 0) { v0 *= QSCALE; v1 *= QSCALE; v2 *= QSCALE; v3 *= QSCALE; }
                    if (p < 2) {
                        s0 = fmaf(v0, v0, s0); s0 = fmaf(v1, v1, s0);
                        s1 = fmaf(v2, v2, s1); s1 = fmaf(v3, v3, s1);
                    } else {
                        s0 = nanmax(s0, nanmax(fabsf(v0), fabsf(v1)));
                        s1 = nanmax(s1, nanmax(fabsf(v2), fabsf(v3)));
                    }
                    pk[2 * g] = pack_bf16(v0, v1); pk[2 * g + 1] = pack_bf16(v2, v3);
                }
                nrm[p * 2 + hh] = nanmax(s0, s1);
                stage_block(hh, pk);
            }
            flush(p);
        }
#pragma unroll
        for (int o = 4; o < 32; o <<= 1) {
#pragma unroll
            for (int i = 0; i < 6; i++) nrm[i] = nanmax(nrm[i], __shfl_xor_sync(0xffffffffu, nrm[i], o));
        }
#pragma unroll
        for (int o = 1; o < 4; o <<= 1) {
#pragma unroll
            for (int i = 0; i < 6; i++) {
                const float other = __shfl_xor_sync(0xffffffffu, nrm[i], o);
                nrm[i] = i < 4 ? nrm[i] + other : nanmax(nrm[i], other);
            }
        }
        if (lane < 6) {
            float v = nrm[0];
#pragma unroll
            for (int q = 1; q < 6; q++) v = lane == q ? nrm[q] : v;
            g_norm[((lane >> 1) * NH + nt * 2 + (lane & 1)) * 128 + mt * 8 + wgm * 4 + warp] = v;
        }
    } else {
#pragma unroll
        for (int hh = 0; hh < 2; hh++) {
            uint32_t pk[8];
#pragma unroll
            for (int g = 0; g < 4; g++) {
                const int j = 16 + hh * 4 + g;
                pk[2 * g] = pack_bf16(a[4 * j], a[4 * j + 1]); pk[2 * g + 1] = pack_bf16(a[4 * j + 2], a[4 * j + 3]);
            }
            stage_block(hh, pk);
        }
        flush(2);
        mbar_wait(sb + B_PHI, phi_ph);
#pragma unroll
        for (int p = 0; p < 2; p++) {
            uint32_t fr[16];
            float f[2][16];
#pragma unroll
            for (int j = 0; j < 8; j++) {
                const int jj = p * 8 + j;
                fr[2 * j] = pack_bf16(a[4 * jj], a[4 * jj + 1]); fr[2 * j + 1] = pack_bf16(a[4 * jj + 2], a[4 * jj + 3]);
            }
            fence_regs_u<16>(fr);
            wg_fence();
#pragma unroll
            for (int hh = 0; hh < 2; hh++) {
                const uint32_t dP = desc_lo(sb + OFF_PHI + hh * 2048, 16);
                wg_rs32t_z(f[hh], fr[8 * hh], fr[8 * hh + 1], fr[8 * hh + 2], fr[8 * hh + 3], dP);
                wg_rs32t(f[hh], fr[8 * hh + 4], fr[8 * hh + 5], fr[8 * hh + 6], fr[8 * hh + 7], dP + 64);
            }
            wg_commit();
            wg_wait<0>();
            fence_regs<16>(f[0]); fence_regs<16>(f[1]);
#pragma unroll
            for (int hh = 0; hh < 2; hh++) {
                uint32_t pk[8];
#pragma unroll
                for (int g = 0; g < 4; g++) {
                    pk[2 * g] = pack_bf16(f[hh][4 * g], f[hh][4 * g + 1]); pk[2 * g + 1] = pack_bf16(f[hh][4 * g + 2], f[hh][4 * g + 3]);
                }
                stage_block(hh, pk);
            }
            flush(p);
        }
        bar_sync(1 + wgm, 128);
    }
}

__device__ __forceinline__ void lin1_task(const uint32_t scr, const int h, const int ch, const int wgm, const int warp, const uint32_t ep1) {
    const int lane = threadIdx.x & 31, tid = threadIdx.x & 127;
    const int r = lane >> 2, c = lane & 3;
    const uint32_t sphi = scr, sv = scr + 32768, sones = sv + 16384;
    if (tid < 64) sts_u4(sones + tid * 16, 0x00003F80u, 0u, 0u, 0u);
    wait_ge(&g_sync.cntA[((h >> 1) * 8 + ch) * CS], ep1 * 4);
    const __nv_bfloat16* gk = g_qkv + ((size_t)((0 * 3 + 1) * NH + h) * SEQ + ch * 256) * 32;
    const __nv_bfloat16* gv = g_qkv + ((size_t)((0 * 3 + 2) * NH + h) * SEQ + ch * 256) * 32;
    uint4 kk[8];
#pragma unroll
    for (int mb = 0; mb < 4; mb++) {
        const int row = mb * 64 + warp * 16 + r;
        kk[2 * mb] = ldcg_u4(gk + (size_t)row * 32 + c * 8);
        kk[2 * mb + 1] = ldcg_u4(gk + (size_t)(row + 8) * 32 + c * 8);
    }
    {
        uint4 vv[8];
#pragma unroll
        for (int i = 0; i < 8; i++) vv[i] = ldcg_u4(gv + (size_t)(tid + 128 * i) * 8);
#pragma unroll
        for (int i = 0; i < 8; i++) {
            const int vr = (tid >> 2) + 32 * i, vc = tid & 3;
            sts_u4(sv + vr * 64 + ((vc ^ ((vr >> 1) & 3)) << 4), vv[i].x, vv[i].y, vv[i].z, vv[i].w);
        }
    }
#pragma unroll
    for (int g = 0; g < 2; g++) {
        uint32_t pos[4][4], neg[4][4];
        hedgehog_rows<4>(kk + 4 * g, pos, neg);
#pragma unroll
        for (int i = 0; i < 4; i++) {
            const int mb = 2 * g + (i >> 1), ra = warp * 16 + r + 8 * (i & 1);
            const uint32_t pa = sphi + mb * 8192 + ra * 128;
            sts_u4(pa + ((c ^ (ra & 7)) << 4), pos[i][0], pos[i][1], pos[i][2], pos[i][3]);
            sts_u4(pa + (((4 + c) ^ (ra & 7)) << 4), neg[i][0], neg[i][1], neg[i][2], neg[i][3]);
        }
    }
    float acc[20];
#pragma unroll
    for (int i = 0; i < 20; i++) acc[i] = 0.f;
    fence_regs<20>(acc);
    fence_async_smem();
    bar_sync(1 + wgm, 128);
    constexpr uint32_t DV_STEP = 64u - (64u << 16);
    const uint32_t dA = desc_lo(sphi, 16);
    const uint32_t dB = desc_lo(sv, sones - sv);
    wg_fence();
#pragma unroll
    for (int kk16 = 0; kk16 < 16; kk16++) wg_ss40tt(acc, dA + kk16 * 128, dB + kk16 * DV_STEP);
    wg_commit();
    wg_wait<0>();
    fence_regs<20>(acc);
    {
        const uint32_t sp = sones + 1024 + warp * 2560;
#pragma unroll
        for (int j = 0; j < 5; j++) {
            asm volatile("st.shared.v2.f32 [%0], {%1, %2};" ::"r"(sp + (r * 40 + j * 8 + c * 2) * 4), "f"(acc[4 * j]), "f"(acc[4 * j + 1]) : "memory");
            asm volatile("st.shared.v2.f32 [%0], {%1, %2};" ::"r"(sp + ((r + 8) * 40 + j * 8 + c * 2) * 4), "f"(acc[4 * j + 2]), "f"(acc[4 * j + 3]) : "memory");
        }
        fence_async_smem();
        __syncwarp();
        bulk_reduce_f32_l0(g_kv + (size_t)((ep1 & 1) * NH + h) * 2560 + warp * 16 * 40, sp, 2560);
        publish_store(&g_sync.cntL1[h * CS]);
    }
    bar_sync(1 + wgm, 128);
}

__device__ __forceinline__ void lin2_task(const TMaps& tm, const uint32_t scr, const int h, const int ch, const int wgm, const int warp, const uint32_t ep1) {
    const int lane = threadIdx.x & 31, tid = threadIdx.x & 127;
    const int r = lane >> 2, c = lane & 3;
    const uint32_t skv = scr;
    const __nv_bfloat16* gq = g_qkv + ((size_t)((0 * 3 + 0) * NH + h) * SEQ + ch * 256) * 32;
    uint4 qq[8];
#pragma unroll
    for (int mb = 0; mb < 4; mb++) {
        const int row = mb * 64 + warp * 16 + r;
        qq[2 * mb] = ldcg_u4(gq + (size_t)row * 32 + c * 8);
        qq[2 * mb + 1] = ldcg_u4(gq + (size_t)(row + 8) * 32 + c * 8);
    }
    uint32_t pos[4][4], neg[4][4];
    hedgehog_rows<4>(qq, pos, neg);
    wait_ge(&g_sync.cntL1[h * CS], ep1 * 32);
    {
        uint4 a[3], bb[3];
#pragma unroll
        for (int it = 0; it < 3; it++) {
            const int idx = min(tid + it * 128, 319);
            const float* src = g_kv + (size_t)((ep1 & 1) * NH + h) * 2560 + idx * 8;
            a[it] = ldcg_u4(src); bb[it] = ldcg_u4(src + 4);
        }
#pragma unroll
        for (int it = 0; it < 3; it++) {
            const int idx = tid + it * 128;
            if (idx < 320) {
                const int f = idx / 5, cg = idx % 5;
                const int half = f >> 5, cc = (f >> 3) & 3, i = f & 7;
                const int kp = half * 32 + 16 * (i >> 2) + 8 * ((i >> 1) & 1) + 2 * cc + (i & 1);
                const uint32_t dsm = skv + (cg == 4 ? 4096 : 0) + kp * 64 + (((cg & 3) ^ ((kp >> 1) & 3)) << 4);
                sts_u4(dsm, pack_bf16(__uint_as_float(a[it].x), __uint_as_float(a[it].y)), pack_bf16(__uint_as_float(a[it].z), __uint_as_float(a[it].w)),
                       pack_bf16(__uint_as_float(bb[it].x), __uint_as_float(bb[it].y)), pack_bf16(__uint_as_float(bb[it].z), __uint_as_float(bb[it].w)));
            }
        }
    }
    fence_async_smem();
    bar_sync(1 + wgm, 128);
    const uint32_t dB = desc_lo(skv, 4096);
#pragma unroll
    for (int g = 0; g < 2; g++) {
        float acc[2][20];
        if (g == 1) hedgehog_rows<4>(qq + 4, pos, neg);
#pragma unroll
        for (int i = 0; i < 4; i++) { fence_regs_u<4>(pos[i]); fence_regs_u<4>(neg[i]); }
        wg_fence();
#pragma unroll
        for (int m = 0; m < 2; m++) {
            const uint32_t *p0 = pos[2 * m], *p1 = pos[2 * m + 1], *n0 = neg[2 * m], *n1 = neg[2 * m + 1];
            wg_rs40t_z(acc[m], p0[0], p1[0], p0[1], p1[1], dB);
            wg_rs40t(acc[m], p0[2], p1[2], p0[3], p1[3], dB + 64);
            wg_rs40t(acc[m], n0[0], n1[0], n0[1], n1[1], dB + 128);
            wg_rs40t(acc[m], n0[2], n1[2], n0[3], n1[3], dB + 192);
        }
        wg_commit();
        wg_wait<0>();
#pragma unroll
        for (int m = 0; m < 2; m++) {
            fence_regs<20>(acc[m]);
            const float d0 = __shfl_sync(0xffffffffu, acc[m][16], lane & ~3) + 1e-6f, d1 = __shfl_sync(0xffffffffu, acc[m][18], lane & ~3) + 1e-6f;
            const float i0 = 1.0f / d0, i1 = 1.0f / d1;
            const float* o = acc[m];
            const uint32_t stg = skv + 8192 + ((2 * g + m) * 4 + warp) * 1024;
            const int strow = (lane & 7) + ((lane >> 3) & 1) * 8;
            const uint32_t sa = stg + strow * 64, x = (strow >> 1) & 3, cc = lane >> 4;
            stsm_x4(sa + ((cc ^ x) << 4), pack_bf16(o[0] * i0, o[1] * i0), pack_bf16(o[2] * i1, o[3] * i1), pack_bf16(o[4] * i0, o[5] * i0), pack_bf16(o[6] * i1, o[7] * i1));
            stsm_x4(sa + (((2 + cc) ^ x) << 4), pack_bf16(o[8] * i0, o[9] * i0), pack_bf16(o[10] * i1, o[11] * i1), pack_bf16(o[12] * i0, o[13] * i0), pack_bf16(o[14] * i1, o[15] * i1));
            fence_async_smem();
            __syncwarp();
            tma_store_l0(&tm.ost, stg, h * 32, ch * 256 + (2 * g + m) * 64 + warp * 16);
        }
    }
    publish_store(&g_sync.cntOA[ch * CS]);
    bar_sync(1 + wgm, 128);
}

template <int BN, bool POLITE>
__device__ __forceinline__ void out_tile(const TMaps& tm, __nv_bfloat16* out, const uint32_t sb, const int prob, const int mt, const int nt,
                                         const int wgm, const int warp, Ring& c, const uint32_t* dep, const uint32_t target,
                                         const uint32_t* dep2, const uint32_t target2) {
    const CUtensorMap* mw = &tm.wo[prob];
    bar_sync(3, 256);
    if (wgm == 0 && warp == 0) {
#pragma unroll
        for (int i = 0; i < OST; i++) {
            const uint32_t st = sb + OFF_MM + i * O_STAGE, fb = sb + B_OFULL + 8 * i;
            mbar_expect_tx_l0(fb, 16384 + BN * 128);
#pragma unroll
            for (int q = 0; q < BN / 64; q++) tma_load_l0(st + 16384 + q * 8192, mw, fb, nt * BN + q * 64, i * 64);
        }
        wait_ge(dep, target);
        fence_async_global();
#pragma unroll
        for (int i = 0; i < OST; i++) tma_load_l0(sb + OFF_MM + i * O_STAGE, &tm.o, sb + B_OFULL + 8 * i, i * 64, prob * SEQ + mt * 128);
    }
    auto refill = [&](int kt, int slot) {
        const int pk = kt + OST;
        if (pk < (dep2 != nullptr ? 12 : 16)) {
            const uint32_t st = sb + OFF_MM + slot * O_STAGE, fb = sb + B_OFULL + 8 * slot;
            mbar_expect_tx_l0(fb, 16384 + BN * 128);
            tma_load_l0(st, &tm.o, fb, pk * 64, prob * SEQ + mt * 128);
#pragma unroll
            for (int q = 0; q < BN / 64; q++) tma_load_l0(st + 16384 + q * 8192, mw, fb, nt * BN + q * 64, pk * 64);
        } else if (dep2 != nullptr && kt == 11) {
#pragma unroll 1
            for (int i = 0; i < OST; i++) {
                const uint32_t st = sb + OFF_MM + i * O_STAGE, fb = sb + B_OFULL + 8 * i;
                mbar_expect_tx_l0(fb, 16384 + BN * 128);
#pragma unroll
                for (int q = 0; q < BN / 64; q++) tma_load_l0(st + 16384 + q * 8192, mw, fb, nt * BN + q * 64, (12 + i) * 64);
            }
            wait_ge(dep2, target2);
            fence_async_global();
#pragma unroll 1
            for (int i = 0; i < OST; i++) tma_load_l0(sb + OFF_MM + i * O_STAGE, &tm.o, sb + B_OFULL + 8 * i, (12 + i) * 64, prob * SEQ + mt * 128);
        }
    };
    float acc[BN / 2];
    mm_tile<BN, true, OUT_BATCH, OST, O_STAGE, B_OFULL, C_OUT>(acc, sb, wgm, c, refill, [](int) {}, [&](int kt) { return prob == 1 && (!POLITE || kt >= 12); });
    uint32_t tidl;
    asm volatile("mov.u32 %0, %%tid.x;" : "=r"(tidl));
    const int lane = tidl & 31;
    const uint32_t stg = sb + OFF_STG + 4096 + ((tidl >> 5) & 7) * 1024;
    const int strow = (lane & 7) + ((lane >> 3) & 1) * 8;
    const uint32_t st_base = stg + strow * 64;
    const uint32_t st_x = (strow >> 1) & 3, st_c = lane >> 4;
    const uint32_t ld_base = stg + (lane >> 2) * 64 + (((lane & 3) ^ ((lane >> 3) & 3)) << 4);
    __nv_bfloat16* dst0 = out + (size_t)(mt * 128 + wgm * 64 + warp * 16 + (lane >> 2)) * 2048 + prob * DM + nt * BN + (lane & 3) * 8;
#pragma unroll
    for (int b = 0; b < BN / 32; b++) {
#pragma unroll
        for (int jj = 0; jj < 2; jj++) {
            const int j = b * 4 + jj * 2;
            stsm_x4(st_base + (((jj * 2 + st_c) ^ st_x) << 4),
                    pack_bf16(acc[4 * j], acc[4 * j + 1]), pack_bf16(acc[4 * j + 2], acc[4 * j + 3]),
                    pack_bf16(acc[4 * j + 4], acc[4 * j + 5]), pack_bf16(acc[4 * j + 6], acc[4 * j + 7]));
        }
        __syncwarp();
        const uint4 v0 = lds_u4(ld_base), v1 = lds_u4(ld_base + 512);
        *reinterpret_cast<uint4*>(dst0 + b * 32) = v0;
        *reinterpret_cast<uint4*>(dst0 + (size_t)8 * 2048 + b * 32) = v1;
        __syncwarp();
    }
}

constexpr int NQKV = 512;
__device__ __forceinline__ void qkv_load_kstep(const TMaps& tm, const uint32_t sb, int T, int pk, int slot) {
    const int prob = T < 256 ? 1 : 0, tt = T & 255;
    const int mt = tt & 15, nt = tt >> 4;
    const uint32_t st = sb + OFF_MM + slot * M_STAGE, fb = sb + B_MFULL + 8 * slot;
    mbar_expect_tx_l0(fb, M_STAGE);
    tma_load_l0(st, &tm.x[prob], fb, pk * 64, mt * 128);
#pragma unroll
    for (int q = 0; q < 3; q++) tma_load_l0(st + 16384 + q * 8192, &tm.w[prob], fb, q * 1024 + nt * 64, pk * 64);
}
__device__ __forceinline__ void mm_role(const TMaps& tm, __nv_bfloat16* out, const uint32_t sb, const int wgm, const int warp, const uint32_t ep1) {
    const int wid = wgm * 4 + warp;
    const int G = gridDim.x;
    Ring c = {0, 0};
    {
        auto load_kstep = [&](int T, int pk, int slot) { qkv_load_kstep(tm, sb, T, pk, slot); };
        auto next_tile = [&](int T) { return T + G; };
        const int T0 = blockIdx.x;
        auto publish = [&](int T) {
            const int tt = T & 255;
            if (T < 256) publish_b_tile(tt >> 4, ep1);
            else signal_add(&g_sync.cntA[((tt >> 4) * 8 + ((tt & 15) >> 1)) * CS]);
        };
        uint32_t phi_ph = 0;
        int j = 0;
        int pend = -1;
#pragma unroll 1
        for (int T = T0; T < NQKV; T = next_tile(T), j++) {
            const int prob = T < 256 ? 1 : 0, tt = T & 255;
            const int mt = tt & 15, nt = tt >> 4;
            float acc[96];
            const int Tn = next_tile(T);
            auto refill = [&](int kt, int slot) {
                const int pk = kt + MST;
                if (pk < 16) load_kstep(T, pk, slot);
                else if (Tn < NQKV) load_kstep(Tn, pk - 16, slot);
            };
            auto at_step = [&](int kt) {
                if (kt == 3) {
                    if (prob == 0 && wid == 0) {
                        mbar_expect_tx_l0(sb + B_PHI, 4096);
                        tma_load_l0(sb + OFF_PHI, &tm.phi, sb + B_PHI, 0, nt * 64);
                    }
                    if (pend >= 0 && warp == 1) publish(pend);
                }
            };
            auto batch = [&](int kt) { return j == 1 && kt < FAST_KSTEPS; };
            if (j == 0) mm_tile<192, false, 1, MST, M_STAGE, B_MFULL, C_MM>(acc, sb, wgm, c, refill, at_step, batch);
            else mm_tile<192, true, QKV_BATCH, MST, M_STAGE, B_MFULL, C_MM>(acc, sb, wgm, c, refill, at_step, batch);
            qkv_epilogue<1024>(acc, sb, sb + OFF_STG, 2048, prob, mt, nt, wgm, warp, ep1, phi_ph);
            if (j == 0) {
                bar_arrive(13 + wgm, 256);
                pend = -1;
            } else {
                if (prob == 1) bar_sync(1 + wgm, 128);
                pend = T;
            }
            if (prob == 0) phi_ph ^= 1;
        }
        if (pend >= 0 && warp == 1) publish(pend);
    }
    bar_sync(3, 256);
    const uint32_t scr = sb + OFF_MM + wgm * (MST * M_STAGE / 2);
#pragma unroll 1
    for (int id = blockIdx.x * 2 + wgm; id < 256; id += 2 * G) lin1_task(scr, id >> 3, id & 7, wgm, warp, ep1);
#pragma unroll 1
    for (int id = blockIdx.x * 2 + wgm; id < 256; id += 2 * G) lin2_task(tm, scr, id >> 3, id & 7, wgm, warp, ep1);
    fence_async_smem();
    Ring co = {0, 0};
#pragma unroll 1
    for (int T = blockIdx.x; T < 128; T += G) out_tile<128, true>(tm, out, sb, 0, T & 15, T >> 4, wgm, warp, co, &g_sync.cntOA[((T & 15) >> 1) * CS], ep1 * 128, nullptr, 0);
#pragma unroll 1
    for (int T = blockIdx.x; T < 128; T += G) out_tile<128, false>(tm, out, sb, 1, T & 15, T >> 4, wgm, warp, co, &g_sync.cntOB[(T & 15) * CS], ep1 * 192, &g_sync.cntOB[(16 + (T & 15)) * CS], ep1 * 64);
}

__global__ void __launch_bounds__(512, 1)
fused_kernel(const __grid_constant__ TMaps tm, __nv_bfloat16* __restrict__ out) {
    extern __shared__ uint8_t smem_raw[];
    const uint32_t sb = (smem_u32(smem_raw) + 1023) & ~1023u;
    const int wg = __shfl_sync(0xffffffffu, threadIdx.x >> 7, 0);
    const int warp = __shfl_sync(0xffffffffu, (threadIdx.x >> 5) & 3, 0);
    if (wg == 2 && warp == 0) {
        if (threadIdx.x == 256) {
            for (int s = 0; s < MST; s++) mbar_init(sb + B_MFULL + 8 * s, 1);
            fence_mbar_init();
        }
        __syncwarp();
#pragma unroll 1
        for (int i = 0; i < MST; i++) qkv_load_kstep(tm, sb, blockIdx.x, i, i);
    }
    if (threadIdx.x == 0) {
        for (int s = 0; s < KVST; s++) mbar_init(sb + B_KVFULL + 8 * s, 1);
        mbar_init(sb + B_QFULL, 1);
        mbar_init(sb + B_PHI, 1);
        for (int s = 0; s < OST; s++) mbar_init(sb + B_OFULL + 8 * s, 1);
        asm volatile("st.shared.u32 [%0], %1;" ::"r"(sb + OFF_FAST + 4), "r"(0u) : "memory");
        for (int s = 0; s < KVST + MST + OST; s++) asm volatile("st.shared.u32 [%0], %1;" ::"r"(sb + C_KV + 4 * s), "r"(0u) : "memory");
        fence_mbar_init();
        prefetch_tmap(&tm.x[1]); prefetch_tmap(&tm.w[1]);
    }
    if (threadIdx.x < 64) {
        sts_u4(sb + OFF_ONES + threadIdx.x * 16, 0x00003F80u, 0u, 0u, 0u);
        fence_async_smem();
    }
    uint32_t ep;
    asm volatile("ld.relaxed.gpu.global.u32 %0, [%1];" : "=r"(ep) : "l"(&g_sync.epoch) : "memory");
    const uint32_t ep1 = __shfl_sync(0xffffffffu, ep, 0) + 1;
    for (int i = blockIdx.x * 512 + threadIdx.x; i < NH * 2560 / 4; i += gridDim.x * 512)
        reinterpret_cast<float4*>(g_kv + (size_t)((ep1 + 1) & 1) * NH * 2560)[i] = make_float4(0.f, 0.f, 0.f, 0.f);
    __syncthreads();
    if (threadIdx.x == 0) {
        uint32_t old;
        asm volatile("atom.relaxed.gpu.global.add.u32 %0, [%1], 1;" : "=r"(old) : "l"(&g_sync.done) : "memory");
        if (old == ep1 * gridDim.x - 1) asm volatile("st.relaxed.gpu.global.u32 [%0], %1;" ::"l"(&g_sync.epoch), "r"(ep1) : "memory");
    }
    __syncwarp();

    if (wg < 2) att_role(tm, sb, wg, warp, ep1);
    else mm_role(tm, out, sb, wg - 2, warp, ep1);

}

typedef CUresult (*EncodeFn)(CUtensorMap*, CUtensorMapDataType, cuuint32_t, void*, const cuuint64_t*, const cuuint64_t*,
                             const cuuint32_t*, const cuuint32_t*, CUtensorMapInterleave, CUtensorMapSwizzle,
                             CUtensorMapL2promotion, CUtensorMapFloatOOBfill);

void make_map(EncodeFn enc, CUtensorMap* m, const void* ptr, uint64_t d0, uint64_t d1, uint32_t b0, uint32_t b1, CUtensorMapSwizzle sw) {
    cuuint64_t dims[2] = {d0, d1};
    cuuint64_t strides[1] = {d0 * 2};
    cuuint32_t box[2] = {b0, b1};
    cuuint32_t es[2] = {1, 1};
    enc(m, CU_TENSOR_MAP_DATA_TYPE_BFLOAT16, 2, const_cast<void*>(ptr), dims, strides, box, es, CU_TENSOR_MAP_INTERLEAVE_NONE, sw,
        CU_TENSOR_MAP_L2_PROMOTION_L2_128B, CU_TENSOR_MAP_FLOAT_OOB_FILL_NONE);
}

}

extern "C" void kernel_launch(void* const* d_in, const int* in_sizes, int n_in, void* d_out, int out_size) {
    (void)in_sizes; (void)n_in; (void)out_size;
    static bool init = false;
    static TMaps tm;
    static int nsm = 132;
    static void* cached[7];
    bool same = init;
    for (int i = 0; i < 7 && same; i++) same = cached[i] == d_in[i];
    if (!same) {
        void* fn = nullptr;
        cudaDriverEntryPointQueryResult qr;
        cudaGetDriverEntryPoint("cuTensorMapEncodeTiled", &fn, cudaEnableDefault, &qr);
        EncodeFn enc = (EncodeFn)fn;
        void* po;
        cudaGetSymbolAddress(&po, g_o);
        make_map(enc, &tm.x[0], d_in[0], 1024, 2048, 64, 128, CU_TENSOR_MAP_SWIZZLE_128B);
        make_map(enc, &tm.x[1], d_in[4], 1024, 2048, 64, 128, CU_TENSOR_MAP_SWIZZLE_128B);
        make_map(enc, &tm.w[0], d_in[1], 3072, 1024, 64, 64, CU_TENSOR_MAP_SWIZZLE_128B);
        make_map(enc, &tm.w[1], d_in[5], 3072, 1024, 64, 64, CU_TENSOR_MAP_SWIZZLE_128B);
        make_map(enc, &tm.phi, d_in[2], 32, 1024, 32, 64, CU_TENSOR_MAP_SWIZZLE_64B);
        make_map(enc, &tm.o, po, 1024, 2 * SEQ, 64, 128, CU_TENSOR_MAP_SWIZZLE_128B);
        make_map(enc, &tm.ost, po, 1024, 2 * SEQ, 32, 16, CU_TENSOR_MAP_SWIZZLE_64B);
        make_map(enc, &tm.wo[0], d_in[3], 1024, 1024, 64, 64, CU_TENSOR_MAP_SWIZZLE_128B);
        make_map(enc, &tm.wo[1], d_in[6], 1024, 1024, 64, 64, CU_TENSOR_MAP_SWIZZLE_128B);
        cudaFuncSetAttribute(fused_kernel, cudaFuncAttributeMaxDynamicSharedMemorySize, SMEM_BYTES);
        int dev = 0;
        cudaGetDevice(&dev);
        cudaDeviceGetAttribute(&nsm, cudaDevAttrMultiProcessorCount, dev);
        if (nsm > 256) nsm = 256;
        for (int i = 0; i < 7; i++) cached[i] = d_in[i];
        init = true;
    }
    void* out_ptr = d_out;
    void* args[2] = {&tm, &out_ptr};
    cudaLaunchKernel((const void*)fused_kernel, dim3(nsm), dim3(512), args, SMEM_BYTES, cudaStreamPerThread);
}
```
